```python
import torch

def _softmax(x, axis=-1):
    return torch.softmax(x, dim=axis)
def _gelu(x):
    return torch.nn.functional.gelu(x, approximate="tanh")
def _silu(x):
    return torch.nn.functional.silu(x)
def _sigmoid(x):
    return torch.sigmoid(x)
def _layernorm(x, axis=-1, eps=1e-5):
    m = x.mean(dim=axis, keepdim=True)
    v = x.var(dim=axis, keepdim=True, unbiased=False)
    return (x - m) / torch.sqrt(v + eps)
def _scatter_add(tgt, idx, src, axis=0):
    return tgt.clone().index_add_(axis, idx, src)
def _segment_sum(src, seg, n):
    out = torch.zeros((n,) + src.shape[1:], dtype=src.dtype)
    return out.index_add_(0, seg, src)
def _pad(x, pw):
    flat = tuple(v for pair in reversed(pw) for v in pair)
    return torch.nn.functional.pad(x, flat)

kernel_name = 'parallel_sum__softmax_full_mha__glu_gated_glu__prompt'

def setup_inputs():

    _w = (lambda a: (lambda t: t.to(torch.bfloat16) if t.is_floating_point() else t)(torch.as_tensor(a)))
    def _A_setup():
        B, S, D = 1, 2048, 576
        return {
            "x": _w((lambda *s: torch.randn(*s, dtype=torch.bfloat16) * 0.05)(B, S, D)),
            "wqkv": _w((lambda *s: torch.randn(*s, dtype=torch.bfloat16) * 0.2)(D, 3 * D)),
            "wo": _w((lambda *s: torch.randn(*s, dtype=torch.bfloat16) * 0.1)(D, D)),
        }
    _A_in = _A_setup()

    def _B_setup():
        B, S, D, F = 1, 2048, 576, 4608
        return {
            "x": _w((lambda *s: torch.randn(*s, dtype=torch.bfloat16) * 0.05)(B, S, D)),
            "w_gate": _w((lambda *s: torch.randn(*s, dtype=torch.bfloat16) * 0.8)(D, F)),
            "w_up": _w((lambda *s: torch.randn(*s, dtype=torch.bfloat16) * 0.1)(D, F)),
            "w_down": _w((lambda *s: torch.randn(*s, dtype=torch.bfloat16) * 0.1)(F, D)),
        }
    _B_in = _B_setup()

    return {
        "A_x": _A_in["x"],
        "A_wqkv": _A_in["wqkv"],
        "A_wo": _A_in["wo"],
        "B_x": _B_in["x"],
        "B_w_gate": _B_in["w_gate"],
        "B_w_up": _B_in["w_up"],
        "B_w_down": _B_in["w_down"],
    }

def reference(A_x, A_wqkv, A_wo, B_x, B_w_gate, B_w_up, B_w_down):
    def _A_ref(x, wqkv, wo):
        B, S, D = x.shape
        H = 32; Dh = D // H
        qkv = (lambda x, *d: x.permute(*d))((x @ wqkv).reshape(B, S, 3, H, Dh), 2, 0, 3, 1, 4)
        q, k, v = qkv[0], qkv[1], qkv[2]
        scale = Dh ** -0.5
        scores = torch.einsum("bhqd,bhkd->bhqk", q, k) * scale
        p = _softmax(scores, axis=-1)
        o = torch.einsum("bhqk,bhkd->bhqd", p, v)
        return (lambda x, *d: x.permute(*d))(o, 0, 2, 1, 3).reshape(B, S, D) @ wo

    def _B_ref(x, w_gate, w_up, w_down):
        g = torch.einsum("bsd,df->bsf", x, w_gate)
        u = torch.einsum("bsd,df->bsf", x, w_up)
        h = _sigmoid(g) * u
        return torch.einsum("bsf,fd->bsd", h, w_down)

    x = A_x
    xn = _layernorm(x, axis=-1)
    return x + _A_ref(xn, A_wqkv, A_wo) + _B_ref(xn, B_w_gate, B_w_up, B_w_down)
```

```cpp
#include <cuda_runtime.h>
#include <cuda_bf16.h>
#include <cuda.h>
#include <stdint.h>

__device__ __forceinline__ void wgmma_ss_n192(float (&d)[96], uint32_t alo, uint32_t blo, int sd) {
  asm volatile("{\n.reg .pred p;\n.reg .b64 da, db;\nsetp.ne.b32 p, %98, 0;\nmov.b64 da, {%96, 0x40000040};\nmov.b64 db, {%97, 0x40000040};\n"
    "wgmma.mma_async.sync.aligned.m64n192k16.f32.bf16.bf16 {%0, %1, %2, %3, %4, %5, %6, %7, %8, %9, %10, %11, %12, %13, %14, %15, %16, %17, %18, %19, %20, %21, %22, %23, %24, %25, %26, %27, %28, %29, %30, %31, %32, %33, %34, %35, %36, %37, %38, %39, %40, %41, %42, %43, %44, %45, %46, %47, %48, %49, %50, %51, %52, %53, %54, %55, %56, %57, %58, %59, %60, %61, %62, %63, %64, %65, %66, %67, %68, %69, %70, %71, %72, %73, %74, %75, %76, %77, %78, %79, %80, %81, %82, %83, %84, %85, %86, %87, %88, %89, %90, %91, %92, %93, %94, %95}, da, db, p, 1, 1, 0, 1;\n}\n"
    : "+f"(d[0]), "+f"(d[1]), "+f"(d[2]), "+f"(d[3]), "+f"(d[4]), "+f"(d[5]), "+f"(d[6]), "+f"(d[7]), "+f"(d[8]), "+f"(d[9]), "+f"(d[10]), "+f"(d[11]), "+f"(d[12]), "+f"(d[13]), "+f"(d[14]), "+f"(d[15]), "+f"(d[16]), "+f"(d[17]), "+f"(d[18]), "+f"(d[19]), "+f"(d[20]), "+f"(d[21]), "+f"(d[22]), "+f"(d[23]), "+f"(d[24]), "+f"(d[25]), "+f"(d[26]), "+f"(d[27]), "+f"(d[28]), "+f"(d[29]), "+f"(d[30]), "+f"(d[31]), "+f"(d[32]), "+f"(d[33]), "+f"(d[34]), "+f"(d[35]), "+f"(d[36]), "+f"(d[37]), "+f"(d[38]), "+f"(d[39]), "+f"(d[40]), "+f"(d[41]), "+f"(d[42]), "+f"(d[43]), "+f"(d[44]), "+f"(d[45]), "+f"(d[46]), "+f"(d[47]), "+f"(d[48]), "+f"(d[49]), "+f"(d[50]), "+f"(d[51]), "+f"(d[52]), "+f"(d[53]), "+f"(d[54]), "+f"(d[55]), "+f"(d[56]), "+f"(d[57]), "+f"(d[58]), "+f"(d[59]), "+f"(d[60]), "+f"(d[61]), "+f"(d[62]), "+f"(d[63]), "+f"(d[64]), "+f"(d[65]), "+f"(d[66]), "+f"(d[67]), "+f"(d[68]), "+f"(d[69]), "+f"(d[70]), "+f"(d[71]), "+f"(d[72]), "+f"(d[73]), "+f"(d[74]), "+f"(d[75]), "+f"(d[76]), "+f"(d[77]), "+f"(d[78]), "+f"(d[79]), "+f"(d[80]), "+f"(d[81]), "+f"(d[82]), "+f"(d[83]), "+f"(d[84]), "+f"(d[85]), "+f"(d[86]), "+f"(d[87]), "+f"(d[88]), "+f"(d[89]), "+f"(d[90]), "+f"(d[91]), "+f"(d[92]), "+f"(d[93]), "+f"(d[94]), "+f"(d[95])
    : "r"(alo), "r"(blo), "r"(sd));
}
template <uint32_t BHI, int SD> __device__ __forceinline__ void wgmma_rs_n64(float (&d)[32], uint32_t a0, uint32_t a1, uint32_t a2, uint32_t a3, uint32_t blo) {
  asm volatile("{\n.reg .b64 db;\nmov.b64 db, {%36, %37};\n"
    "wgmma.mma_async.sync.aligned.m64n64k16.f32.bf16.bf16 {%0, %1, %2, %3, %4, %5, %6, %7, %8, %9, %10, %11, %12, %13, %14, %15, %16, %17, %18, %19, %20, %21, %22, %23, %24, %25, %26, %27, %28, %29, %30, %31}, {%32,%33,%34,%35}, db, %38, 1, 1, 0;\n}\n"
    : "+f"(d[0]), "+f"(d[1]), "+f"(d[2]), "+f"(d[3]), "+f"(d[4]), "+f"(d[5]), "+f"(d[6]), "+f"(d[7]), "+f"(d[8]), "+f"(d[9]), "+f"(d[10]), "+f"(d[11]), "+f"(d[12]), "+f"(d[13]), "+f"(d[14]), "+f"(d[15]), "+f"(d[16]), "+f"(d[17]), "+f"(d[18]), "+f"(d[19]), "+f"(d[20]), "+f"(d[21]), "+f"(d[22]), "+f"(d[23]), "+f"(d[24]), "+f"(d[25]), "+f"(d[26]), "+f"(d[27]), "+f"(d[28]), "+f"(d[29]), "+f"(d[30]), "+f"(d[31])
    : "r"(a0), "r"(a1), "r"(a2), "r"(a3), "r"(blo), "n"(BHI), "n"(SD));
}
template <uint32_t BHI, int SD> __device__ __forceinline__ void wgmma_rs_n24(float (&d)[12], uint32_t a0, uint32_t a1, uint32_t a2, uint32_t a3, uint32_t blo) {
  asm volatile("{\n.reg .b64 db;\nmov.b64 db, {%16, %17};\n"
    "wgmma.mma_async.sync.aligned.m64n24k16.f32.bf16.bf16 {%0, %1, %2, %3, %4, %5, %6, %7, %8, %9, %10, %11}, {%12,%13,%14,%15}, db, %18, 1, 1, 1;\n}\n"
    : "+f"(d[0]), "+f"(d[1]), "+f"(d[2]), "+f"(d[3]), "+f"(d[4]), "+f"(d[5]), "+f"(d[6]), "+f"(d[7]), "+f"(d[8]), "+f"(d[9]), "+f"(d[10]), "+f"(d[11])
    : "r"(a0), "r"(a1), "r"(a2), "r"(a3), "r"(blo), "n"(BHI), "n"(SD));
}

#define GP(...) __VA_ARGS__
#define HINT "20000"
namespace {

constexpr int SEQ = 2048, DM = 576, FF = 4608, HW = FF + DM;
constexpr int NCTA = 132, NATT = 128;
#define P_C1 26
#define P_C2 27
#define P_F 21
constexpr int NL = 8, C1 = P_C1, C2 = P_C2, CF = P_F;
constexpr int MAXSLOT = 160;
constexpr int GST = 4, GSTB = 40960;
constexpr int KST = 5, KSTB = 6144;
constexpr int QB = 128 * 36;
constexpr int OFF_STG = GST * GSTB;
constexpr int OFF_KV = OFF_STG + 32768;
constexpr int OFF_Q = OFF_KV + KST * KSTB;
constexpr int OFF_BAR = OFF_Q + QB;
constexpr int SMEM_BYTES = OFF_BAR + 512;
constexpr int BH = 16384, BH2 = 12288;
constexpr float MBIAS = 72.f;

constexpr int FL_LN = 0;
constexpr int FL_QKV = 512;
constexpr int FL_H = 1024;
constexpr int FL_P = FL_H + 16 * 96;
constexpr int FL_DONE = FL_P + MAXSLOT;
constexpr int FL_TOTAL = FL_DONE + 32;

struct Sched {
  uint8_t nseg, own, om, on, np, ps[3];
  uint8_t sm[4], sn[4], k0[4], k1[4], slot[4];
  uint8_t kc;
  uint8_t ne[4];
};
struct Params {
  CUtensorMap xn, xn64, H, out, wqkv, wg1, wu1, wg2, wu2, wd, wo, xin;
  const __nv_bfloat16* x;
  uint32_t zero, pad;
  Sched sch[NCTA];
};

__device__ __align__(1024) __nv_bfloat16 g_xn[SEQ * DM];
__device__ __align__(1024) __nv_bfloat16 g_H[SEQ * HW];
__device__ __align__(1024) uint8_t g_q[32 * SEQ * 36];
__device__ __align__(1024) uint8_t g_kv[32 * 32 * KSTB];
__device__ __align__(1024) uint4 g_part[MAXSLOT * 3072];
__device__ int g_flags[FL_TOTAL];
#define STAMP(i)
#define TIC(v)
#define TOC(acc, v)
#define PUT(i, val)

__device__ __forceinline__ void wg_fence() { asm volatile("wgmma.fence.sync.aligned;" ::: "memory"); }
__device__ __forceinline__ void wg_commit() { asm volatile("wgmma.commit_group.sync.aligned;" ::: "memory"); }
template <int N> __device__ __forceinline__ void wg_wait() { asm volatile("wgmma.wait_group.sync.aligned %0;" ::"n"(N) : "memory"); }
template <int N> __device__ __forceinline__ void pin(float (&d)[N]) {
#pragma unroll
  for (int i = 0; i < N; i++) asm volatile("" : "+f"(d[i])::"memory");
}
template <int N> __device__ __forceinline__ void pin(uint32_t (&d)[N]) {
#pragma unroll
  for (int i = 0; i < N; i++) asm volatile("" : "+r"(d[i])::"memory");
}
__device__ __forceinline__ uint32_t desc_lo(uint32_t addr, uint32_t lbo) { return ((addr & 0x3FFFF) >> 4) | ((lbo >> 4) << 16); }
__device__ __forceinline__ float ex2(float x) { float r; asm("ex2.approx.ftz.f32 %0, %1;" : "=f"(r) : "f"(x)); return r; }
__device__ __forceinline__ float tanhf_fast(float x) { float r; asm("tanh.approx.f32 %0, %1;" : "=f"(r) : "f"(x)); return r; }
__device__ __forceinline__ uint32_t pack2(float lo, float hi) { uint32_t r; asm("cvt.rn.bf16x2.f32 %0, %1, %2;" : "=r"(r) : "f"(hi), "f"(lo)); return r; }
__device__ __forceinline__ float bf_lo(uint32_t v) { float r; asm("shl.b32 %0, %1, 16;" : "=f"(r) : "r"(v)); return r; }
__device__ __forceinline__ float bf_hi(uint32_t v) { float r; asm("and.b32 %0, %1, 0xffff0000;" : "=f"(r) : "r"(v)); return r; }
__device__ __forceinline__ float bf_rn(float v) { return __bfloat162float(__float2bfloat16_rn(v)); }
__device__ __forceinline__ float fdiv(float a, float b) { float r; asm("div.full.f32 %0, %1, %2;" : "=f"(r) : "f"(a), "f"(b)); return r; }
__device__ __forceinline__ float fsqrt(float a) { float r; asm("sqrt.approx.f32 %0, %1;" : "=f"(r) : "f"(a)); return r; }
__device__ __forceinline__ int lane_id() { int l; asm volatile("mov.u32 %0, %%laneid;" : "=r"(l)); return l; }
__device__ __forceinline__ uint32_t clk32() { uint32_t c; asm volatile("mov.u32 %0, %%clock;" : "=r"(c)); return c; }

__device__ __forceinline__ void mbar_init(uint32_t a, uint32_t c) { asm volatile("mbarrier.init.shared::cta.b64 [%0], %1;" ::"r"(a), "r"(c) : "memory"); }
__device__ __forceinline__ void mbar_arrive(uint32_t a) { asm volatile("mbarrier.arrive.shared::cta.b64 _, [%0];" ::"r"(a) : "memory"); }
__device__ __forceinline__ bool mbar_test(uint32_t a, uint32_t ph) {
  uint32_t ok;
  asm volatile("{\n.reg .pred p;\nmbarrier.test_wait.parity.shared::cta.b64 p, [%1], %2;\nselp.u32 %0, 1, 0, p;\n}\n" : "=r"(ok) : "r"(a), "r"(ph) : "memory");
  return ok;
}
__device__ __forceinline__ void mbar_wait(uint32_t a, uint32_t ph) {
  asm volatile("{\n.reg .pred p;\n.reg .u32 n;\nmbarrier.try_wait.parity.shared::cta.b64 p, [%0], %1;\n@p bra D_%=;\nmov.u32 n, 0;\n"
               "W_%=:\nmbarrier.try_wait.parity.shared::cta.b64 p, [%0], %1, " HINT ";\n@p bra D_%=;\n"
               "add.u32 n, n, 1;\nsetp.lt.u32 p, n, 200000;\n@p bra W_%=;\ntrap;\nD_%=:\n}\n" ::"r"(a), "r"(ph) : "memory");
}
#define ELECT "{\n.reg .pred e;\nelect.sync _|e, 0xffffffff;\n@e "
__device__ __forceinline__ uint64_t policy_stream() {
  uint64_t p; asm("createpolicy.fractional.L2::evict_first.b64 %0, 1.0;" : "=l"(p)); return p;
}
__device__ __forceinline__ void expect1(uint32_t a, uint32_t b) { asm volatile(ELECT "mbarrier.arrive.expect_tx.shared::cta.b64 _, [%0], %1;\n}\n" ::"r"(a), "r"(b) : "memory"); }
__device__ __forceinline__ void tma2d(uint32_t dst, const CUtensorMap* m, int c0, int c1, uint32_t bar) {
  asm volatile(ELECT "cp.async.bulk.tensor.2d.shared::cluster.global.mbarrier::complete_tx::bytes [%0], [%1, {%3, %4}], [%2];\n}\n"
               ::"r"(dst), "l"(m), "r"(bar), "r"(c0), "r"(c1) : "memory");
}
__device__ __forceinline__ void tma3d_mc(uint32_t dst, const CUtensorMap* m, int c0, int c1, int c2, uint32_t bar) {
  asm volatile(ELECT "cp.async.bulk.tensor.3d.shared::cluster.global.mbarrier::complete_tx::bytes.multicast::cluster [%0], [%1, {%3, %4, %5}], [%2], %6;\n}\n"
               ::"r"(dst), "l"(m), "r"(bar), "r"(c0), "r"(c1), "r"(c2), "h"((uint16_t)3) : "memory");
}
__device__ __forceinline__ void tma3d_mc_stream(uint32_t dst, const CUtensorMap* m, int c0, int c1, int c2, uint32_t bar, uint64_t pol) {
  asm volatile(ELECT "cp.async.bulk.tensor.3d.shared::cluster.global.mbarrier::complete_tx::bytes.multicast::cluster.L2::cache_hint [%0], [%1, {%3, %4, %5}], [%2], %6, %7;\n}\n"
               ::"r"(dst), "l"(m), "r"(bar), "r"(c0), "r"(c1), "r"(c2), "h"((uint16_t)3), "l"(pol) : "memory");
}
__device__ __forceinline__ void bulk_load(uint32_t dst, const void* src, uint32_t bytes, uint32_t bar, uint64_t pol) {
  asm volatile(ELECT "cp.async.bulk.shared::cluster.global.mbarrier::complete_tx::bytes.L2::cache_hint [%0], [%1], %2, [%3], %4;\n}\n"
               ::"r"(dst), "l"(src), "r"(bytes), "r"(bar), "l"(pol) : "memory");
}
__device__ __forceinline__ void bulk_load_mc(uint32_t dst, const void* src, uint32_t bytes, uint32_t bar, uint64_t pol) {
  asm volatile(ELECT "cp.async.bulk.shared::cluster.global.mbarrier::complete_tx::bytes.multicast::cluster.L2::cache_hint [%0], [%1], %2, [%3], %4, %5;\n}\n"
               ::"r"(dst), "l"(src), "r"(bytes), "r"(bar), "h"((uint16_t)3), "l"(pol) : "memory");
}
__device__ __forceinline__ uint32_t map_peer(uint32_t a, uint32_t rank) { uint32_t r; asm("mapa.shared::cluster.u32 %0, %1, %2;" : "=r"(r) : "r"(a), "r"(rank)); return r; }
__device__ __forceinline__ void arrive_cluster(uint32_t a) { asm volatile("mbarrier.arrive.relaxed.cluster.shared::cluster.b64 _, [%0];" ::"r"(a) : "memory"); }
__device__ __forceinline__ void arrive_cluster1(uint32_t a) { asm volatile(ELECT "mbarrier.arrive.relaxed.cluster.shared::cluster.b64 _, [%0];\n}\n" ::"r"(a) : "memory"); }
__device__ __forceinline__ void release_stage(uint32_t a, int lane) { if (lane < 2) arrive_cluster(map_peer(a, lane)); }
__device__ __forceinline__ void cluster_sync() { asm volatile("barrier.cluster.arrive.relaxed.aligned;\nbarrier.cluster.wait.aligned;" ::: "memory"); }
__device__ __forceinline__ int uni(int v) { return __shfl_sync(0xffffffffu, v, 0); }
__device__ __forceinline__ void tma2d_store(const CUtensorMap* m, int c0, int c1, uint32_t src) {
  asm volatile("cp.async.bulk.tensor.2d.global.shared::cta.bulk_group [%0, {%2, %3}], [%1];" ::"l"(m), "r"(src), "r"(c0), "r"(c1) : "memory");
}
__device__ __forceinline__ void pf3d(const CUtensorMap* m, int c0, int c1, int c2) {
  asm volatile("cp.async.bulk.prefetch.tensor.3d.L2.global [%0, {%1, %2, %3}];" ::"l"(m), "r"(c0), "r"(c1), "r"(c2) : "memory");
}
__device__ __forceinline__ void bulk_commit() { asm volatile("cp.async.bulk.commit_group;" ::: "memory"); }
__device__ __forceinline__ void bulk_wait0() { asm volatile("cp.async.bulk.wait_group 0;" ::: "memory"); }
__device__ __forceinline__ void fence_async_glob() { asm volatile("fence.proxy.async.global;" ::: "memory"); }
__device__ __forceinline__ void fence_cta() { asm volatile("fence.acq_rel.cta;" ::: "memory"); }
__device__ __forceinline__ void fence_release() { asm volatile("fence.release.gpu;" ::: "memory"); }
__device__ __forceinline__ void red_relaxed(int* p) { asm volatile("red.relaxed.gpu.global.add.s32 [%0], 1;" ::"l"(p) : "memory"); }
__device__ __forceinline__ void bar_arrive(int id, int n) { asm volatile("bar.arrive %0, %1;" ::"r"(id), "r"(n) : "memory"); }
__device__ __forceinline__ void bar_sync(int id, int n) { asm volatile("bar.sync %0, %1;" ::"r"(id), "r"(n) : "memory"); }
__device__ __forceinline__ void fence_async_smem() { asm volatile("fence.proxy.async.shared::cta;" ::: "memory"); }
__device__ __forceinline__ void red_release(int* p) { asm volatile("red.release.gpu.global.add.s32 [%0], 1;" ::"l"(p) : "memory"); }
__device__ __forceinline__ int ld_acquire(const int* p) { int v; asm volatile("ld.acquire.gpu.global.s32 %0, [%1];" : "=r"(v) : "l"(p) : "memory"); return v; }
__device__ __forceinline__ void stsm4(uint32_t a, uint32_t r0, uint32_t r1, uint32_t r2, uint32_t r3) {
  asm volatile("stmatrix.sync.aligned.m8n8.x4.shared.b16 [%0], {%1,%2,%3,%4};" ::"r"(a), "r"(r0), "r"(r1), "r"(r2), "r"(r3) : "memory");
}
__device__ __forceinline__ void ldsm4(uint32_t a, uint32_t& r0, uint32_t& r1, uint32_t& r2, uint32_t& r3) {
  asm volatile("ldmatrix.sync.aligned.m8n8.x4.shared.b16 {%0,%1,%2,%3}, [%4];" : "=r"(r0), "=r"(r1), "=r"(r2), "=r"(r3) : "r"(a) : "memory");
}
__device__ __forceinline__ uint32_t lds32(uint32_t a) { uint32_t v; asm volatile("ld.shared.u32 %0, [%1];" : "=r"(v) : "r"(a) : "memory"); return v; }
__device__ __forceinline__ uint4 lds128(uint32_t a) {
  uint4 v; asm volatile("ld.shared.v4.u32 {%0,%1,%2,%3}, [%4];" : "=r"(v.x), "=r"(v.y), "=r"(v.z), "=r"(v.w) : "r"(a) : "memory"); return v;
}
__device__ __forceinline__ void poll_ge(const int* p, int target) {
  const uint32_t t0 = clk32();
  while (!__all_sync(0xffffffffu, ld_acquire(p) >= target)) { __nanosleep(20); if (clk32() - t0 > 0x60000000u) __trap(); }
}

__device__ __forceinline__ void layernorm_row(const uint32_t (&v)[9], int row, int lane) {
  float s = 0.f;
#pragma unroll
  for (int i = 0; i < 9; i++) s += bf_lo(v[i]) + bf_hi(v[i]);
#pragma unroll
  for (int o = 16; o; o >>= 1) s += __shfl_xor_sync(0xffffffffu, s, o);
  const float mean = s * (1.f / DM);
  float q = 0.f;
#pragma unroll
  for (int i = 0; i < 9; i++) { float a = bf_lo(v[i]) - mean, b = bf_hi(v[i]) - mean; q += a * a + b * b; }
#pragma unroll
  for (int o = 16; o; o >>= 1) q += __shfl_xor_sync(0xffffffffu, q, o);
  const float mb = bf_rn(mean);
  const float den = bf_rn(fsqrt(bf_rn(bf_rn(q * (1.f / DM)) + 1e-5f)));
  uint32_t* o = reinterpret_cast<uint32_t*>(g_xn + (size_t)row * DM);
#pragma unroll
  for (int i = 0; i < 9; i++) o[lane + 32 * i] = pack2(fdiv(bf_rn(bf_lo(v[i]) - mb), den), fdiv(bf_rn(bf_hi(v[i]) - mb), den));
  fence_async_glob();
  __syncwarp();
  if (lane == 0) red_release(g_flags + FL_LN + (row >> 7) * 32);
}

__device__ __forceinline__ void attn_row_slow(int head, int row, int lane) {
  const uint8_t* qp = g_q + (size_t)head * (SEQ * 36) + row * 36;
  float q[18], o[18];
#pragma unroll
  for (int d = 0; d < 18; d += 2) {
    uint32_t v = *reinterpret_cast<const volatile uint32_t*>(qp + d * 2);
    q[d] = bf_lo(v); q[d + 1] = bf_hi(v); o[d] = 0.f; o[d + 1] = 0.f;
  }
  float m = -INFINITY, l = 0.f;
#pragma unroll 1
  for (int key = lane; key < SEQ; key += 32) {
    const uint8_t* kp = g_kv + (size_t)head * (32 * KSTB) + (key >> 6) * KSTB + ((key >> 3) & 7) * 384 + (key & 7) * 16;
    float s = 0.f;
#pragma unroll
    for (int d = 0; d < 18; d += 2) {
      uint32_t v = *reinterpret_cast<const volatile uint32_t*>(kp + (d >> 3) * 128 + (d & 7) * 2);
      s = fmaf(q[d], bf_lo(v), s); s = fmaf(q[d + 1], bf_hi(v), s);
    }
    const float mn = fmaxf(m, s), c = ex2(m - mn), p = ex2(s - mn);
    m = mn; l = l * c + p;
#pragma unroll
    for (int d = 0; d < 18; d += 2) {
      uint32_t v = *reinterpret_cast<const volatile uint32_t*>(kp + 3072 + (d >> 3) * 128 + (d & 7) * 2);
      o[d] = fmaf(p, bf_lo(v), o[d] * c); o[d + 1] = fmaf(p, bf_hi(v), o[d + 1] * c);
    }
  }
  float M = m;
#pragma unroll
  for (int t = 16; t; t >>= 1) M = fmaxf(M, __shfl_xor_sync(0xffffffffu, M, t));
  const float c = ex2(m - M);
  l *= c;
#pragma unroll
  for (int t = 16; t; t >>= 1) l += __shfl_xor_sync(0xffffffffu, l, t);
  uint32_t* dst = reinterpret_cast<uint32_t*>(g_H + (size_t)row * HW + FF + head * 18);
#pragma unroll
  for (int d = 0; d < 18; d += 2) {
    float a = o[d] * c, b = o[d + 1] * c;
#pragma unroll
    for (int t = 16; t; t >>= 1) { a += __shfl_xor_sync(0xffffffffu, a, t); b += __shfl_xor_sync(0xffffffffu, b, t); }
    if (lane == 0) dst[d >> 1] = pack2(fdiv(a, l), fdiv(b, l));
  }
}

#define GTH 0
template <bool BOTH, int TH = 0>
__device__ __forceinline__ void gemm_run(float (&a0)[96], float (&a1)[96], int nk, int keep, int& st, uint32_t& ph, uint32_t dA,
                                         uint32_t bar_full, int lane, uint32_t& gw) {
  constexpr uint32_t AB = (BH >> 4) + (255u << 16);
  uint32_t da = dA + st * (GSTB >> 4);
  uint32_t rel = 0;
  int kb = 0;
  pin(a0); pin(a1);
#pragma unroll 1
  do {
    wg_fence();
    wgmma_ss_n192(a0, da, da + AB, kb | keep);
    wg_commit();
    wg_wait<1>();
    if (rel) release_stage(rel, lane);
    if (BOTH) {
      wgmma_ss_n192(a1, da + 512, da + AB, kb | keep);
      wg_commit();
      wg_wait<(TH & 1) ? 0 : 1>();
    }
    rel = bar_full + 32 + 8 * st;
    if (++st == GST) { st = 0; ph ^= 1; }
    bool ready = false;
#pragma unroll
    for (int k = 1; k < 4; k++) {
      if (k == 3) ready = mbar_test(bar_full + 8 * st, ph);
      wgmma_ss_n192(a0, da + 2 * k, da + AB + (k >> 1) * (BH2 >> 4) + (k & 1) * 128, 1);
      wg_commit();
      if (BOTH) {
        wg_wait<1>();
        wgmma_ss_n192(a1, da + 512 + 2 * k, da + AB + (k >> 1) * (BH2 >> 4) + (k & 1) * 128, 1);
        wg_commit();
      }
      if (k == 1) wg_wait<(TH & 2) ? 0 : 1>();
      if (k == 2) wg_wait<(TH & 4) ? 0 : 1>();
    }
    da = dA + st * (GSTB >> 4);
    if (++kb < nk && !ready) { TIC(t0); mbar_wait(bar_full + 8 * st, ph); TOC(gw, t0); }
    wg_wait<(TH & 8) ? 0 : 1>();
  } while (kb < nk);
  wg_wait<0>();
  pin(a0); pin(a1);
  release_stage(rel, lane);
}

__device__ __forceinline__ void qkv_scatter(uint32_t tile, int rb, int a, int w, int hoff, int hstep, int lane) {
  const int r8 = lane >> 2, j = lane & 3;
  const int h0 = ((a * 64 * 3641) >> 16) + hoff;
  uint8_t* const qb = g_q + (rb * 8 + r8) * 36 + j * 4;
  uint8_t* const kb = g_kv + (rb >> 3) * KSTB + (rb & 7) * 384 + r8 * 16 + j * 4;
  const uint32_t row = tile + (w * 16 + r8) * 400;
#pragma unroll 1
  for (int h = h0; h * 18 < a * 64 + 64; h += hstep) {
    uint32_t v[3][6];
    bool data[3];
#pragma unroll
    for (int c = 0; c < 3; c++) {
      const int col = h * 18 + c * 8 + 2 * j - a * 64;
      data[c] = (unsigned)col < 64u && (c < 2 || j == 0);
      const uint32_t src = row + (data[c] ? col : 0) * 2;
#pragma unroll
      for (int e = 0; e < 6; e++) v[c][e] = lds32(src + (e >> 1) * 128 + (e & 1) * 3200);
    }
    const bool pad = j > 0 && (unsigned)(h * 18 + 16 - a * 64) < 64u;
    if (j > 0) { v[2][2] = v[2][3] = j == 1 ? 0x3f803f80u : 0u; v[2][4] = v[2][5] = j == 1 ? 0x00003f80u : 0u; }
    uint8_t* const qp = qb + h * (SEQ * 36);
    uint8_t* const kp = kb + h * (32 * KSTB);
#pragma unroll
    for (int c = 0; c < 3; c++) {
      if (data[c]) { *reinterpret_cast<uint32_t*>(qp + c * 16) = v[c][0]; *reinterpret_cast<uint32_t*>(qp + c * 16 + 288) = v[c][1]; }
      if (data[c] || (c == 2 && pad)) {
        *reinterpret_cast<uint32_t*>(kp + c * 128) = v[c][2]; *reinterpret_cast<uint32_t*>(kp + c * 128 + 384) = v[c][3];
        *reinterpret_cast<uint32_t*>(kp + c * 128 + 3072) = v[c][4]; *reinterpret_cast<uint32_t*>(kp + c * 128 + 3456) = v[c][5];
      }
    }
  }
}
__device__ __forceinline__ void qkv_scatter_small(uint32_t tile, int rb, int a, int w, int lane) {
  const int r8 = lane >> 2, j = lane & 3;
  const uint32_t row = tile + (w * 16 + r8) * 400;
  const uint32_t qo = (rb * 8 + r8) * 36 + j * 4, ko = (rb >> 3) * KSTB + (rb & 7) * 384 + r8 * 16 + j * 4;
#pragma unroll 1
  for (int i = ((a * 64 * 3641) >> 16) * 3;; i++) {
    const int h = (i * 683) >> 11, c = i - h * 3, col0 = h * 18 + c * 8 - a * 64, col = col0 + 2 * j;
    if (col0 >= 64) break;
    const bool data = (unsigned)col < 64u && (c < 2 || j == 0), pad = c == 2 && j > 0 && col0 >= 0;
    const uint32_t src = row + (data ? col : 0) * 2;
    uint32_t v[6];
#pragma unroll
    for (int e = 0; e < 6; e++) v[e] = lds32(src + (e >> 1) * 128 + (e & 1) * 3200);
    if (pad) { v[2] = v[3] = j == 1 ? 0x3f803f80u : 0u; v[4] = v[5] = j == 1 ? 0x00003f80u : 0u; }
    uint8_t* const qp = g_q + (qo + h * (SEQ * 36) + c * 16);
    uint8_t* const kp = g_kv + (ko + h * (32 * KSTB) + c * 128);
    if (data) { *reinterpret_cast<uint32_t*>(qp) = v[0]; *reinterpret_cast<uint32_t*>(qp + 288) = v[1]; }
    if (data || pad) {
      *reinterpret_cast<uint32_t*>(kp) = v[2]; *reinterpret_cast<uint32_t*>(kp + 384) = v[3];
      *reinterpret_cast<uint32_t*>(kp + 3072) = v[4]; *reinterpret_cast<uint32_t*>(kp + 3456) = v[5];
    }
  }
}

__global__ void __cluster_dims__(2, 1, 1) __launch_bounds__(512, 1) fused_kernel(const __grid_constant__ Params P) {
  extern __shared__ __align__(1024) uint8_t smem_raw[];
  const uint32_t sb = (uint32_t)__cvta_generic_to_shared(smem_raw);
  if (sb & 1023u) __trap();
  const uint32_t bar_gfull = sb + OFF_BAR, bar_gempty = bar_gfull + 32;
  const uint32_t bar_kfull = bar_gfull + 256, bar_kempty = bar_kfull + 80;
  const uint32_t bar_gdone = bar_gfull + 160, bar_gfree = bar_gfull + 168, bar_odone = bar_gfull + 176, bar_qdone = bar_gfull + 184;
  const uint32_t bar_kpeer = bar_kfull + 160;
  const int tid = threadIdx.x;
  const int warp = __shfl_sync(0xffffffffu, tid >> 5, 0);
  const int wg = warp >> 2;
  const int cta = blockIdx.x;
  const bool att = cta < NATT;
  const int cm = cta & 15, cj = cta >> 4;
  const Sched& sch = P.sch[cta];
  const int nq = att ? 2 : 4, ngu = att ? 6 : 0;
  const int qa = att ? cta >> 5 : 8, qrow = att ? (cta & 31) * 64 : (cta - NATT) * 512;

  uint32_t xv[9];
  if (att) {
    const uint32_t* xr = reinterpret_cast<const uint32_t*>(P.x + (size_t)(cta * 16 + warp) * DM);
#pragma unroll
    for (int i = 0; i < 9; i++) xv[i] = __ldg(xr + (tid & 31) + 32 * i);
  }
  if (tid == 384) {
    for (int i = 0; i < GST; i++) { mbar_init(bar_gfull + 8 * i, 1); mbar_init(bar_gempty + 8 * i, 8); }
        for (int i = 0; i <= KST; i++) { mbar_init(bar_kfull + 8 * i, 1); mbar_init(bar_kempty + 8 * i, 8); }
    mbar_init(bar_gdone, 4); mbar_init(bar_gfree, 1); mbar_init(bar_odone, 8); mbar_init(bar_qdone, 8);
    for (int i = 0; i < KST; i++) mbar_init(bar_kpeer + 8 * i, 1);
    asm volatile("fence.mbarrier_init.release.cluster;" ::: "memory");
    fence_async_smem();
    STAMP(0);
  }
  if (tid >= 480 && tid < 492) asm volatile("prefetch.tensormap [%0];" ::"l"(&P.xn + (tid - 480)) : "memory");
  __syncwarp();
  cluster_sync();
  const int rank = cta & 1;
  if (warp == 12)
    for (int i = 0; i < GST; i++) {
      expect1(bar_gfull + 8 * i, att ? GSTB - 8192 : GSTB);
      tma3d_mc(sb + i * GSTB + BH + rank * BH2, &P.wqkv, qa * 64, i * 64 + rank * 32, 0, bar_gfull + 8 * i);
    }
  if (tid == 416 && cm < 10) pf3d(&P.wqkv, qa * 64, GST * 64 + cm * 32, 0);
  __syncwarp();
  if (att) layernorm_row(xv, cta * 16 + warp, tid & 31);

  if (wg == 3) {
    asm volatile("setmaxnreg.dec.sync.aligned.u32 24;");
    const int pw = warp & 3, lane = lane_id();
    const bool el = lane == 0;
    if (pw == 0) {
      int st = 0; uint32_t ph = 1;
      const uint64_t pol = policy_stream();
      auto acquire = [&](uint32_t bytes) -> uint32_t {
        mbar_wait(bar_gempty + 8 * st, ph);
        expect1(bar_gfull + 8 * st, bytes);
        return sb + st * GSTB;
      };
      auto advance = [&]() { if (++st == GST) { st = 0; ph ^= 1; } };
#pragma unroll 1
      for (int t = 0; t < nq; t++) {
        const int a = uni(att ? qa + 4 * t : 8), row = uni(att ? qrow : qrow + t * 128);
        const CUtensorMap* mx = att ? &P.xn64 : &P.xn;
        int kb = 0;
        poll_ge(g_flags + FL_LN + (row >> 7) * 32, 128);
        fence_async_glob();
        if (t == 0) {
          STAMP(1);
          for (int i = 0; i < GST; i++) tma2d(sb + i * GSTB, mx, i * 64, row, bar_gfull + 8 * i);
          kb = GST; ph ^= 1;
        }
        st = uni(st); ph = uni(ph); kb = uni(kb);
#pragma unroll 1
        for (; kb < 9; kb++) {
          const uint32_t s = acquire(att ? GSTB - 8192 : GSTB);
          tma2d(s, mx, kb * 64, row, bar_gfull + 8 * st);
          tma3d_mc(s + BH + rank * BH2, &P.wqkv, a * 64, kb * 64 + rank * 32, 0, bar_gfull + 8 * st);
          advance();
        }
      }
      if (att) { poll_ge(g_flags + FL_LN + cm * 32, 128); fence_async_glob(); }
#pragma unroll 1
      for (int t = 0; t < ngu; t++) {
        const int a0 = uni((cj + 8 * (t >> 1)) * 3), hf = uni(t & 1);
        const CUtensorMap* m2 = hf ? &P.wu2 : &P.wg2; const CUtensorMap* m1 = hf ? &P.wg1 : &P.wu1;
        const int x2 = a0 + hf, x1 = a0 + 2 * hf;
        if (t == 2 && lane < 4) {
          const int b = cta + 128 * lane;
          if (b < 432) pf3d(&P.wd, 0, (b / 3) * 32, (b % 3) * 3);
          else if (b < 486) pf3d(&P.wo, 0, ((b - 432) / 3) * 32, ((b - 432) % 3) * 3);
        }
        st = uni(st); ph = uni(ph);
#pragma unroll 1
        for (int kb = 0; kb < 9; kb++) {
          const uint32_t s = acquire(GSTB), b = bar_gfull + 8 * st;
          tma2d(s, &P.xn, kb * 64, cm * 128, b);
          tma3d_mc_stream(s + BH + rank * BH2, m2, 0, kb * 64 + rank * 32, x2, b, pol);
          tma3d_mc_stream(s + BH + rank * BH2 + 8192, m1, 0, kb * 64 + rank * 32, x1, b, pol);
          advance();
        }
      }
      auto wait_h = [&](int m, int kb, int k1) -> int {
        const uint32_t t0 = clk32();
        const int i = kb + lane;
        uint32_t b;
        while (true) {
          bool ok = false;
          if (i < k1) ok = ld_acquire(g_flags + FL_H + m * 96 + i) >= (i < 72 ? 1 : 4 + (i & 1));
          b = __ballot_sync(0xffffffffu, ok);
          if (b & 1) break;
          __nanosleep(100);
          if (clk32() - t0 > 0x60000000u) __trap();
        }
        fence_async_glob();
        return uni(kb + (b == 0xffffffffu ? 32 : __ffs(~b) - 1));
      };
      auto down_range = [&](int m, int n, int k0, int k1) {
#pragma unroll 1
        for (int kb = k0; kb < k1;) {
          const int ready = wait_h(m, kb, k1);
          st = uni(st); ph = uni(ph); kb = uni(kb); m = uni(m); n = uni(n);
          const CUtensorMap* mw = kb < 72 ? &P.wd : &P.wo;
          const int y0 = rank * 32 - (kb < 72 ? 0 : 72 * 64);
#pragma unroll 1
          for (; kb < ready; kb++) {
            const uint32_t s = acquire(GSTB), b = bar_gfull + 8 * st;
            tma2d(s, &P.H, kb * 64, m * 128, b);
            tma3d_mc(s + BH + rank * BH2, mw, 0, kb * 64 + y0, n * 3, b);
            advance();
          }
        }
      };
#pragma unroll 1
      for (int i = 0; i < sch.nseg; i++) {
        const int va = sch.k0[i], vb = sch.k1[i], ne = sch.ne[i];
#pragma unroll 1
        for (int h = 0; h < 2; h++)
          down_range(sch.sm[i], sch.sn[i], h ? (va > ne ? va : ne) + 48 - ne : va, h ? vb + 48 - ne : (vb < ne ? vb : ne));
      }
      if (sch.own) {
        const int m = sch.om, n = sch.on;
#pragma unroll 1
        for (int h = 0; h < 4; h++) down_range(m, n, h == 0 ? 72 : h == 1 ? sch.kc - NL : h == 2 ? 48 + NL : 76, h == 0 ? 76 : h == 1 ? 48 : h == 2 ? 72 : 78);
        for (int c = 0; c < 2; c++) {
          const uint32_t s = acquire(c ? 16384 : 32768);
          tma2d(s, &P.xin, n * 192 + c * 128, m * 128, bar_gfull + 8 * st);
          if (!c) tma2d(s + 16384, &P.xin, n * 192 + 64, m * 128, bar_gfull + 8 * st);
          advance();
        }
#pragma unroll 1
        for (int p = 0; p < sch.np; p++) {
          const int slot = sch.ps[p];
          poll_ge(g_flags + FL_P + slot, 1);
          fence_async_glob();
          for (int c = 0; c < 2; c++) {
            const uint32_t s = acquire(24576);
            bulk_load(s, g_part + slot * 3072 + c * 1536, 24576, bar_gfull + 8 * st, pol);
            advance();
          }
        }
        const int st0 = st;
        for (int kb = 6; kb < 9; kb++) {
          const uint32_t s = acquire(GSTB);
          tma3d_mc(s + BH + rank * BH2, &P.wo, 0, kb * 64 + rank * 32, n * 3, bar_gfull + 8 * st);
          advance();
        }
#pragma unroll 1
        for (int kb = 78; kb < 81;) {
          const int ready = wait_h(m, kb, 81);
          for (; kb < ready; kb++) {
            const int s2 = (st0 + kb - 78) & (GST - 1);
            tma2d(sb + s2 * GSTB, &P.H, kb * 64, m * 128, bar_gfull + 8 * s2);
          }
        }
      }
    } else if (pw == 1) {
      if (att) {
        const uint64_t pol = policy_stream();
        const uint32_t peer = map_peer(bar_kpeer, rank ^ 1);
        uint32_t st = 0, ph = 0;
        int m = 0;
#pragma unroll 1
        for (int r = 0; r < 5; r++) {
          if (r < 4) {
            const int head = r * 8 + cj, atom = (head * 18 + (lane & 1) * 17) >> 6;
            poll_ge(g_flags + FL_QKV + atom * 32, atom < 8 ? 256 : 128);
            fence_async_glob();
            mbar_wait(bar_kempty + 8 * KST, (r & 1) ^ 1);
            expect1(bar_kfull + 8 * KST, QB);
            bulk_load(sb + OFF_Q, g_q + head * (SEQ * 36) + cm * QB, QB, bar_kfull + 8 * KST, pol);
            if (r == 0) STAMP(2);
          }
          const int mend = uni(r < 3 ? r * 32 + 27 : (r == 3 ? 0 : 129));
          st = uni(st); ph = uni(ph); m = uni(m);
#pragma unroll 1
          for (; m < mend; m++) {
            const int n = m - rank;
            mbar_wait(bar_kempty + 8 * st, ph ^ 1);
            arrive_cluster1(peer + 8 * st);
            expect1(bar_kfull + 8 * st, (unsigned)(m - 1) < 127u ? KSTB : 3072);
            mbar_wait(bar_kpeer + 8 * st, ph);
            if ((unsigned)n < 128u)
              bulk_load_mc(sb + OFF_KV + st * KSTB + rank * 3072, g_kv + (uint32_t)((((n >> 5) * 8 + cj) * 32 + (n & 31)) * KSTB + rank * 3072), 3072,
                           bar_kfull + 8 * st, pol);
            if (++st == KST) { st = 0; ph ^= 1; }
          }
        }
      }
    } else if (pw == 2) {
      const int ns = att ? nq - 1 : 0, nt = ns + ngu + sch.nseg;
      for (int e = 0; e < nt; e++) {
        const int u = e - ns;
        mbar_wait(bar_gdone, e & 1);
        if (u < 0) {
          qkv_scatter_small(sb + OFF_STG, (qrow >> 3), qa + 4, 0, lane);
          qkv_scatter_small(sb + OFF_STG, (qrow >> 3) + 2, qa + 4, 1, lane);
          bar_sync(3, 64);
        }
        if (el) {
          if (u < 0) {
            fence_async_glob();
            fence_release();
            asm volatile("red.relaxed.gpu.global.add.s32 [%0], 8;" ::"l"(g_flags + FL_QKV + (qa + 4) * 32) : "memory");
          } else if (u < ngu) {
            const int a0 = (cj + 8 * (u >> 1)) * 3;
            if (u & 1) { tma2d_store(&P.H, (a0 + 1) * 64, cm * 128, sb + OFF_STG + 16384); tma2d_store(&P.H, (a0 + 2) * 64, cm * 128, sb + OFF_STG); }
            else tma2d_store(&P.H, a0 * 64, cm * 128, sb + OFF_STG);
            bulk_commit(); bulk_wait0();
            fence_release();
            if (u & 1) { red_relaxed(g_flags + FL_H + cm * 96 + a0 + 1); red_relaxed(g_flags + FL_H + cm * 96 + a0 + 2); }
            else red_relaxed(g_flags + FL_H + cm * 96 + a0);
          } else {
            fence_async_glob();
            red_release(g_flags + FL_P + sch.slot[u - ngu]);
          }
          mbar_arrive(bar_gfree);
          if (u == ngu - 1) STAMP(35);
          if (e == nt - 1) STAMP(36);
        }
        __syncwarp();
      }
    } else {
      if (att) {
        if (lane < 7) {
          const int b = cm + 16 * lane;
          if (b < 108) pf3d(b < 54 ? &P.wg1 : &P.wu1, 0, ((b % 54) / 3) * 32, cj * 3 + b % 3);
        }
        mbar_wait(bar_gdone, 0);
        qkv_scatter_small(sb + OFF_STG, (qrow >> 3) + 4, qa + 4, 2, lane);
        qkv_scatter_small(sb + OFF_STG, (qrow >> 3) + 6, qa + 4, 3, lane);
        fence_cta();
        bar_sync(3, 64);
        STAMP(34);
        for (int r = 0; r < 4; r++) {
          mbar_wait(bar_odone, r & 1);
          if (el) {
            const int head = r * 8 + cj, a0 = (head * 18) >> 6, a1 = (head * 18 + 17) >> 6;
            fence_async_glob();
            fence_release();
            red_relaxed(g_flags + FL_H + cm * 96 + 72 + a0);
            if (a1 != a0) red_relaxed(g_flags + FL_H + cm * 96 + 72 + a1);
          }
          __syncwarp();
        }
      }
    }
    if (pw == 0 || (pw == 1 && att)) {
      int old = 0;
      if (el) { __threadfence(); old = atomicAdd(g_flags + FL_DONE, 1); __threadfence(); }
      old = __shfl_sync(0xffffffffu, old, 0);
      if (old == NCTA + NATT - 1) for (int i = lane; i < FL_TOTAL; i += 32) g_flags[i] = 0;
    }
  } else if (wg >= 1) {
    const int lane = lane_id();
#pragma unroll 1
    for (int t = 0; t < (att ? 1 : nq); t++) {
      bar_sync(1, 384);
      if (att) qkv_scatter(sb + OFF_STG, (qrow >> 3) + (warp & 3) * 2, qa, warp & 3, wg - 1, 2, lane);
      else qkv_scatter(sb + OFF_STG, (qrow >> 3) + t * 16 + (warp - 4) * 2, 8, warp - 4, 0, 1, lane);
      fence_async_glob();
      __syncwarp();
      if (lane == 0) { red_release(g_flags + FL_QKV + qa * 32); mbar_arrive(bar_qdone); }
      if (warp == 4) STAMP(32);
    }
    if (att) {
      const int wa = warp - 4;
      const int r8 = lane >> 2, j = lane & 3;
      const uint32_t kvd = __shfl_sync(0xffffffffu, desc_lo(sb + OFF_KV, 0), 0);
      const uint32_t kb0 = __shfl_sync(0xffffffffu, bar_kfull, 0);
      constexpr uint32_t DK = 8u << 16, DK2 = 16, DV = (24u << 16) + 192;
      const uint32_t qa = sb + OFF_Q + (wa * 16 + r8) * 36 + j * 4;
      uint32_t q[8], p[16];
      float s[32], s2[32], o[12];
      auto load_q = [&](int r) {
        mbar_wait(kb0 + 8 * KST, r & 1);
        q[0] = lds32(qa); q[1] = lds32(qa + 288); q[2] = lds32(qa + 16); q[3] = lds32(qa + 304);
        q[4] = j == 0 ? lds32(qa + 32) : 0u; q[5] = j == 0 ? lds32(qa + 320) : 0u; q[6] = 0u; q[7] = 0u;
      };
      load_q(0);
      mbar_wait(kb0, 0);
      pin(q);
      wg_fence();
      wgmma_rs_n64<24, 0>(s, q[0], q[1], q[2], q[3], kvd + DK);
      wgmma_rs_n64<24, 1>(s, q[4], q[5], q[6], q[7], kvd + DK2);
      wg_commit();
      mbar_wait(kb0 + 8, 0);
      wg_wait<0>();
      pin(s);
#pragma unroll
      for (int i = 0; i < 32; i++) s2[i] = 0.f;
#pragma unroll
      for (int i = 0; i < 16; i++) p[i] = 0u;
      uint32_t cur = 1, prev = 0, nph = 0;
      auto step = [&](float (&a)[32], float (&b)[32], bool last) {
        const uint32_t d = kvd + cur * (KSTB >> 4);
        const uint32_t nxt = cur + 1 == KST ? 0 : cur + 1;
        if (nxt == 0) nph ^= 1;
        pin(b); pin(q);
        wg_fence();
        wgmma_rs_n64<24, 0>(b, q[0], q[1], q[2], q[3], d + DK);
        wgmma_rs_n64<24, 1>(b, q[4], q[5], q[6], q[7], d + DK2);
        wg_commit();
#pragma unroll
        for (int i = 0; i < 32; i++) a[i] = ex2(a[i]);
        pin(a);
        wg_wait<1>();
        pin(p); pin(o);
        if (lane == 0) mbar_arrive(kb0 + 80 + 8 * prev);
        const bool ready = mbar_test(kb0 + 8 * nxt, nph);
#pragma unroll
        for (int i = 0; i < 16; i++) p[i] = pack2(a[2 * i], a[2 * i + 1]);
        pin(p);
        wg_fence();
#pragma unroll
        for (int k = 0; k < 4; k++)
          wgmma_rs_n24<8, 1>(o, p[4 * k], p[4 * k + 1], p[4 * k + 2], p[4 * k + 3], d + DV + k * 48);
        wg_commit();
        if (!ready && !last) mbar_wait(kb0 + 8 * nxt, nph);
        wg_wait<1>();
        pin(b);
        prev = cur; cur = nxt;
      };
#pragma unroll 1
      for (int r = 0; r < 4; r++) {
        const int head = r * 8 + cj;
        TIC(tb);
        if (lane == 0) mbar_arrive(kb0 + 80 + 8 * KST);
        {
          float m0 = fmaxf(s[0], s[1]), m1 = fmaxf(s[2], s[3]);
#pragma unroll
          for (int i = 4; i < 32; i += 4) { m0 = fmaxf(m0, fmaxf(s[i], s[i + 1])); m1 = fmaxf(m1, fmaxf(s[i + 2], s[i + 3])); }
          m0 = fmaxf(m0, __shfl_xor_sync(0xffffffffu, m0, 1)); m1 = fmaxf(m1, __shfl_xor_sync(0xffffffffu, m1, 1));
          m0 = fmaxf(m0, __shfl_xor_sync(0xffffffffu, m0, 2)); m1 = fmaxf(m1, __shfl_xor_sync(0xffffffffu, m1, 2));
          m0 = -(m0 + MBIAS); m1 = -(m1 + MBIAS);
          const float h0 = bf_rn(m0), h1 = bf_rn(m1), l0 = bf_rn(m0 - h0), l1 = bf_rn(m1 - h1);
          if (j == 1) { q[4] = pack2(h0, l0); q[5] = pack2(h1, l1); }
          m0 = h0 + l0; m1 = h1 + l1;
#pragma unroll
          for (int i = 0; i < 32; i += 4) { s[i] += m0; s[i + 1] += m0; s[i + 2] += m1; s[i + 3] += m1; }
        }
#pragma unroll
        for (int i = 0; i < 12; i++) o[i] = 0.f;
        TOC(aw, tb);
#pragma unroll 1
        for (int n = 0; n < 16; n++) {
          step(s, s2, false);
          if (n == 15 && r < 3) load_q(r + 1);
          step(s2, s, n == 15 && r == 3);
        }
        wg_wait<0>();
        pin(o); pin(s);
        TIC(te);
        const float l0 = __shfl_sync(0xffffffffu, o[8], (lane & ~3) | 1), l1 = __shfl_sync(0xffffffffu, o[10], (lane & ~3) | 1);
        float lo0 = fminf(fminf(fabsf(o[0]), fabsf(o[1])), fminf(fabsf(o[4]), fabsf(o[5])));
        float lo1 = fminf(fminf(fabsf(o[2]), fabsf(o[3])), fminf(fabsf(o[6]), fabsf(o[7])));
        float z0 = (o[0] + o[1] + o[4] + o[5]) * 0.f, z1 = (o[2] + o[3] + o[6] + o[7]) * 0.f;
        if (j == 0) {
          lo0 = fminf(lo0, fminf(fabsf(o[8]), fabsf(o[9]))); lo1 = fminf(lo1, fminf(fabsf(o[10]), fabsf(o[11])));
          z0 += (o[8] + o[9]) * 0.f; z1 += (o[10] + o[11]) * 0.f;
        }
        const bool ok0 = l0 >= 0x1p-90f && l0 <= 0x1p125f && lo0 >= l0 * 0x1p-33f && z0 == 0.f;
        const bool ok1 = l1 >= 0x1p-90f && l1 <= 0x1p125f && lo1 >= l1 * 0x1p-33f && z1 == 0.f;
        const int row = cm * 128 + wa * 16 + r8;
        {
          const float i0 = fdiv(1.f, l0), i1 = fdiv(1.f, l1);
          uint32_t* d0 = reinterpret_cast<uint32_t*>(g_H + (size_t)row * HW + FF + head * 18) + j;
          uint32_t* d1 = d0 + 8 * (HW / 2);
          d0[0] = pack2(o[0] * i0, o[1] * i0); d0[4] = pack2(o[4] * i0, o[5] * i0);
          d1[0] = pack2(o[2] * i1, o[3] * i1); d1[4] = pack2(o[6] * i1, o[7] * i1);
          if (j == 0) { d0[8] = pack2(o[8] * i0, o[9] * i0); d1[8] = pack2(o[10] * i1, o[11] * i1); }
        }
        const uint32_t bad0 = __ballot_sync(0xffffffffu, !ok0), bad1 = __ballot_sync(0xffffffffu, !ok1);
        if (bad0 | bad1) {
          __syncwarp();
#pragma unroll 1
          for (int rr = 0; rr < 16; rr++)
            if (((rr < 8 ? bad0 : bad1) >> ((rr & 7) * 4)) & 15u) attn_row_slow(head, cm * 128 + wa * 16 + rr, lane);
        }
        fence_cta();
        __syncwarp();
        if (lane == 0) mbar_arrive(bar_odone);
        TOC(aw, te);
        if (wa == 0) { STAMP(4 + r); PUT(56, aw); PUT(57, am); PUT(59, nr); PUT(60 + r, ak); }
        if (wa == 4) { PUT(24 + r, clk32() - c0); PUT(28, nr); PUT(58, clk32() - c0); }
      }
    }
  } else {
    asm volatile("setmaxnreg.inc.sync.aligned.u32 232;");
    const int lane = lane_id();
    float acc0[96], acc1[96];
#pragma unroll
    for (int i = 0; i < 96; i++) { acc0[i] = 0.f; acc1[i] = 0.f; }
    int st = 0; uint32_t ph = 0;
    const uint32_t dA = __shfl_sync(0xffffffffu, desc_lo(sb, 16), 0);
    const uint32_t soff = (warp * 16 + (lane & 15)) * 128 + (((lane >> 4) ^ (lane & 7)) << 4);
    const int ntask = nq + ngu + sch.nseg + sch.own;
    uint32_t gw = 0;
#pragma unroll 1
    for (int t = 0; t < ntask; t++) {
      const int u = t - nq, sg = u - ngu;
      const bool is_own = sg == sch.nseg;
      int nk = 9, keep = 0;
      if (sg >= 0) {
        nk = is_own ? 78 - sch.kc : sch.k1[sg] - sch.k0[sg];
      }
#pragma unroll 1
      for (int part = 0;; part++) {
        { TIC(t0); mbar_wait(bar_gfull + 8 * st, ph); TOC(gw, t0); }
        if (att && t < 2) gemm_run<false>(acc0, acc1, nk, keep, st, ph, dA, bar_gfull, lane, gw);
        else if (GTH && att && !part) gemm_run<true, GTH>(acc0, acc1, nk, keep, st, ph, dA, bar_gfull, lane, gw);
        else gemm_run<true>(acc0, acc1, nk, keep, st, ph, dA, bar_gfull, lane, gw);
        GP(if (warp == 0) { STAMP(part ? 41 : 8 + 2 * (t - nq + 1 < 0 ? 0 : t - nq + 1)); PUT(44 + (t - nq + 1 < 0 ? 0 : t - nq + 1), gw); })
        if (!is_own || part) break;
#pragma unroll
        for (int c = 0; c < 2; c++) {
          mbar_wait(bar_gfull + 8 * st, ph);
          uint32_t dep = 0;
          auto addx = [&](float (&acc)[96], uint32_t base) {
#pragma unroll
            for (int g = c * 16; g < (c ? 24 : 16); g += 2) {
              uint32_t w[4];
              ldsm4((base + ((g >> 3) & 1) * 16384) ^ ((g & 7) << 4), w[0], w[1], w[2], w[3]);
              dep |= w[3];
#pragma unroll
              for (int i = 0; i < 4; i++) { acc[4 * g + 2 * i] += bf_lo(w[i]); acc[4 * g + 2 * i + 1] += bf_hi(w[i]); }
            }
          };
          addx(acc0, sb + st * GSTB + soff); addx(acc1, sb + st * GSTB + soff + 8192);
          release_stage(bar_gempty + 8 * st + (dep & P.zero), lane);
          if (++st == GST) { st = 0; ph ^= 1; }
        }
#pragma unroll 1
        for (int pp = 0; pp < sch.np; pp++) {
          auto add = [&](float (&acc)[96]) {
            mbar_wait(bar_gfull + 8 * st, ph);
            const uint32_t a = sb + st * GSTB + (warp * 32 + lane) * 16;
            uint32_t dep = 0;
#pragma unroll
            for (int i = 0; i < 12; i++) {
              const uint4 v = lds128(a + i * 2048);
              dep |= v.w;
              acc[8 * i] += bf_lo(v.x); acc[8 * i + 1] += bf_hi(v.x); acc[8 * i + 2] += bf_lo(v.y); acc[8 * i + 3] += bf_hi(v.y);
              acc[8 * i + 4] += bf_lo(v.z); acc[8 * i + 5] += bf_hi(v.z); acc[8 * i + 6] += bf_lo(v.w); acc[8 * i + 7] += bf_hi(v.w);
            }
            release_stage(bar_gempty + 8 * st + (dep & P.zero), lane);
            if (++st == GST) { st = 0; ph ^= 1; }
          };
          add(acc0); add(acc1);
        }
        pin(acc0); pin(acc1);
        GP(if (warp == 0) STAMP(40);)
        nk = 3; keep = 1;
      }
      if (is_own) {
        bar_sync(12, 128);
        auto st_out = [&](float (&acc)[96], uint32_t base) {
#pragma unroll
          for (int g = 0; g < 24; g += 2)
            stsm4((base + (g >> 3) * 16384) ^ ((g & 7) << 4), pack2(acc[4 * g], acc[4 * g + 1]), pack2(acc[4 * g + 2], acc[4 * g + 3]),
                  pack2(acc[4 * g + 4], acc[4 * g + 5]), pack2(acc[4 * g + 6], acc[4 * g + 7]));
        };
        st_out(acc0, sb + soff); st_out(acc1, sb + soff + 8192);
        fence_async_smem();
        bar_sync(12, 128);
        if (warp == 0 && lane == 0) {
          for (int a = 0; a < 3; a++) tma2d_store(&P.out, sch.on * 192 + a * 64, sch.om * 128, sb + a * 16384);
          bulk_commit(); bulk_wait0();
        }
        if (warp == 0) STAMP(42);
        break;
      }
      const int na = att ? 1 : nq;
      if (t > 0) { if (t <= na) mbar_wait(bar_qdone, (t - 1) & 1); else mbar_wait(bar_gfree, (t - na - 1) & 1); }
      if (u < 0) {
        const float qs = 0.23570226039551584f * 1.4426950408889634f;
        auto st_qkv = [&](float (&acc)[96], uint32_t pa) {
#pragma unroll
          for (int g = 0; g < 24; g += 2) {
            const float f = g < 8 ? qs : 1.f;
            stsm4(pa + g * 16, pack2(acc[4 * g] * f, acc[4 * g + 1] * f), pack2(acc[4 * g + 2] * f, acc[4 * g + 3] * f),
                  pack2(acc[4 * g + 4] * f, acc[4 * g + 5] * f), pack2(acc[4 * g + 6] * f, acc[4 * g + 7] * f));
          }
        };
        const uint32_t pa = sb + OFF_STG + (warp * 16 + (lane & 15)) * 400 + (lane >> 4) * 16;
        st_qkv(acc0, pa);
        if (t < na) {
          if (!att) st_qkv(acc1, pa + 64 * 400);
          bar_arrive(1, 384);
        } else {
          __syncwarp();
          if (lane == 0) mbar_arrive(bar_gdone);
        }
      } else {
        if (sg < 0) {
          auto sig = [](float g) { return fmaf(tanhf_fast(0.5f * g), 0.5f, 0.5f); };
          auto even = [&](float (&acc)[96], uint32_t s0) {
#pragma unroll
            for (int g = 0; g < 8; g += 2) {
              uint32_t h[4], w[4];
#pragma unroll
              for (int i = 0; i < 4; i++) {
                const int e = 4 * g + 2 * i;
                h[i] = pack2(sig(acc[e]) * acc[64 + e], sig(acc[e + 1]) * acc[65 + e]);
                w[i] = pack2(sig(acc[32 + e]), sig(acc[33 + e]));
              }
              stsm4(s0 ^ (g << 4), h[0], h[1], h[2], h[3]);
              stsm4((s0 + 16384) ^ (g << 4), w[0], w[1], w[2], w[3]);
            }
          };
          auto odd = [&](float (&acc)[96], uint32_t s0) {
#pragma unroll
            for (int g = 0; g < 8; g += 2) {
              uint32_t h[4], w[4];
              ldsm4((s0 + 16384) ^ (g << 4), w[0], w[1], w[2], w[3]);
#pragma unroll
              for (int i = 0; i < 4; i++) {
                const int e = 4 * g + 2 * i;
                h[i] = pack2(sig(acc[64 + e]) * acc[32 + e], sig(acc[65 + e]) * acc[33 + e]);
                w[i] = pack2(bf_lo(w[i]) * acc[e], bf_hi(w[i]) * acc[e + 1]);
              }
              stsm4(s0 ^ (g << 4), h[0], h[1], h[2], h[3]);
              stsm4((s0 + 16384) ^ (g << 4), w[0], w[1], w[2], w[3]);
            }
          };
          const uint32_t s0 = sb + OFF_STG + soff;
          if (!(u & 1)) { even(acc0, s0); even(acc1, s0 + 8192); } else { odd(acc0, s0); odd(acc1, s0 + 8192); }
          fence_async_smem();
        } else {
          uint4* pp = g_part + sch.slot[sg] * 3072 + warp * 32 + lane;
#pragma unroll
          for (int i = 0; i < 12; i++) {
            pp[i * 128] = make_uint4(pack2(acc0[8 * i], acc0[8 * i + 1]), pack2(acc0[8 * i + 2], acc0[8 * i + 3]),
                                     pack2(acc0[8 * i + 4], acc0[8 * i + 5]), pack2(acc0[8 * i + 6], acc0[8 * i + 7]));
            pp[i * 128 + 1536] = make_uint4(pack2(acc1[8 * i], acc1[8 * i + 1]), pack2(acc1[8 * i + 2], acc1[8 * i + 3]),
                                            pack2(acc1[8 * i + 4], acc1[8 * i + 5]), pack2(acc1[8 * i + 6], acc1[8 * i + 7]));
          }
          fence_cta();
        }
        __syncwarp();
        if (lane == 0) mbar_arrive(bar_gdone);
      }
      GP(if (warp == 0) { STAMP(9 + 2 * (t - nq + 1 < 0 ? 0 : t - nq + 1)); if (t == 0) STAMP(33); })
    }
  }
  __syncwarp();
  cluster_sync();
}

typedef CUresult (*EncodeFn)(CUtensorMap*, CUtensorMapDataType, cuuint32_t, void*, const cuuint64_t*, const cuuint64_t*, const cuuint32_t*,
                             const cuuint32_t*, CUtensorMapInterleave, CUtensorMapSwizzle, CUtensorMapL2promotion, CUtensorMapFloatOOBfill);

void make_map(EncodeFn enc, CUtensorMap* m, const void* ptr, int rank, uint64_t d0, uint64_t d1, uint64_t d2, uint64_t s1, uint64_t s2,
              uint32_t b0, uint32_t b1, uint32_t b2) {
  cuuint64_t gd[3] = {d0, d1, d2}, gs[2] = {s1, s2};
  cuuint32_t bd[3] = {b0, b1, b2}, es[3] = {1, 1, 1};
  enc(m, CU_TENSOR_MAP_DATA_TYPE_BFLOAT16, rank, const_cast<void*>(ptr), gd, gs, bd, es, CU_TENSOR_MAP_INTERLEAVE_NONE,
      CU_TENSOR_MAP_SWIZZLE_128B, CU_TENSOR_MAP_L2_PROMOTION_L2_256B, CU_TENSOR_MAP_FLOAT_OOB_FILL_NONE);
}

void build_schedule(Sched* s) {
  for (int i = 0; i < NCTA; i++) s[i] = Sched{};
  int nslot = 0;
  auto add = [&](int pair, int tp, int k0, int k1, int kc) {
    for (int r = 0; r < 2; r++) {
      Sched& c = s[2 * pair + r];
      c.sm[c.nseg] = 2 * (tp / 3) + r; c.sn[c.nseg] = tp % 3; c.k0[c.nseg] = k0; c.k1[c.nseg] = k1; c.ne[c.nseg] = kc - NL;
      c.slot[c.nseg] = nslot; c.nseg++;
      Sched& o = s[2 * tp + r];
      o.ps[o.np++] = nslot++; o.kc = kc;
    }
  };
  for (int t = 0; t < 48; t++) { s[t].own = 1; s[t].om = 2 * (t / 6) + (t & 1); s[t].on = (t / 2) % 3; }
  for (int t = 0; t < 8; t++) {
    add(64 + t / 4, t, 0, CF, CF + C2);
    add(24 + t, t, CF, CF + C2, CF + C2);
  }
  for (int t = 8; t < 24; t++) {
    add(32 + 2 * (t - 8), t, 0, C1, 2 * C1);
    add(33 + 2 * (t - 8), t, C1, 2 * C1, 2 * C1);
  }
}

}

extern "C" void kernel_launch(void* const* d_in, const int* in_sizes, int n_in, void* d_out, int out_size) {
  static EncodeFn enc = nullptr;
  if (!enc) {
    void* f = nullptr; cudaDriverEntryPointQueryResult q;
    cudaGetDriverEntryPoint("cuTensorMapEncodeTiled", &f, cudaEnableDefault, &q);
    enc = (EncodeFn)f;
    cudaFuncSetAttribute(fused_kernel, cudaFuncAttributeMaxDynamicSharedMemorySize, SMEM_BYTES);
  }
  void *xn, *H;
  cudaGetSymbolAddress(&xn, g_xn);
  cudaGetSymbolAddress(&H, g_H);
  Params P;
  P.x = (const __nv_bfloat16*)d_in[0];
  P.zero = 0; P.pad = 0;
  make_map(enc, &P.xn, xn, 2, DM, SEQ, 1, DM * 2, 0, 64, 128, 1);
  make_map(enc, &P.xn64, xn, 2, DM, SEQ, 1, DM * 2, 0, 64, 64, 1);
  make_map(enc, &P.xin, d_in[0], 2, DM, SEQ, 1, DM * 2, 0, 64, 128, 1);
  make_map(enc, &P.H, H, 2, HW, SEQ, 1, HW * 2, 0, 64, 128, 1);
  make_map(enc, &P.out, d_out, 2, DM, SEQ, 1, DM * 2, 0, 64, 128, 1);
  make_map(enc, &P.wqkv, d_in[1], 3, DM, DM, 3, 3 * DM * 2, DM * 2, 64, 32, 3);
  make_map(enc, &P.wg1, d_in[4], 3, 64, DM, 72, FF * 2, 128, 64, 32, 1);
  make_map(enc, &P.wu1, d_in[5], 3, 64, DM, 72, FF * 2, 128, 64, 32, 1);
  make_map(enc, &P.wg2, d_in[4], 3, 64, DM, 72, FF * 2, 128, 64, 32, 2);
  make_map(enc, &P.wu2, d_in[5], 3, 64, DM, 72, FF * 2, 128, 64, 32, 2);
  make_map(enc, &P.wd, d_in[6], 3, 64, FF, 9, DM * 2, 128, 64, 32, 3);
  make_map(enc, &P.wo, d_in[2], 3, 64, DM, 9, DM * 2, 128, 64, 32, 3);
  build_schedule(P.sch);
  fused_kernel<<<NCTA, 512, SMEM_BYTES>>>(P);
}
```

```cpp
#include <cuda_runtime.h>
#include <cuda_bf16.h>
#include <cuda.h>
#include <stdint.h>

__device__ __forceinline__ void wgmma_ss_n192(float (&d)[96], uint32_t alo, uint32_t blo, int sd) {
  asm volatile("{\n.reg .pred p;\n.reg .b64 da, db;\nsetp.ne.b32 p, %98, 0;\nmov.b64 da, {%96, 0x40000040};\nmov.b64 db, {%97, 0x40000040};\n"
    "wgmma.mma_async.sync.aligned.m64n192k16.f32.bf16.bf16 {%0, %1, %2, %3, %4, %5, %6, %7, %8, %9, %10, %11, %12, %13, %14, %15, %16, %17, %18, %19, %20, %21, %22, %23, %24, %25, %26, %27, %28, %29, %30, %31, %32, %33, %34, %35, %36, %37, %38, %39, %40, %41, %42, %43, %44, %45, %46, %47, %48, %49, %50, %51, %52, %53, %54, %55, %56, %57, %58, %59, %60, %61, %62, %63, %64, %65, %66, %67, %68, %69, %70, %71, %72, %73, %74, %75, %76, %77, %78, %79, %80, %81, %82, %83, %84, %85, %86, %87, %88, %89, %90, %91, %92, %93, %94, %95}, da, db, p, 1, 1, 0, 1;\n}\n"
    : "+f"(d[0]), "+f"(d[1]), "+f"(d[2]), "+f"(d[3]), "+f"(d[4]), "+f"(d[5]), "+f"(d[6]), "+f"(d[7]), "+f"(d[8]), "+f"(d[9]), "+f"(d[10]), "+f"(d[11]), "+f"(d[12]), "+f"(d[13]), "+f"(d[14]), "+f"(d[15]), "+f"(d[16]), "+f"(d[17]), "+f"(d[18]), "+f"(d[19]), "+f"(d[20]), "+f"(d[21]), "+f"(d[22]), "+f"(d[23]), "+f"(d[24]), "+f"(d[25]), "+f"(d[26]), "+f"(d[27]), "+f"(d[28]), "+f"(d[29]), "+f"(d[30]), "+f"(d[31]), "+f"(d[32]), "+f"(d[33]), "+f"(d[34]), "+f"(d[35]), "+f"(d[36]), "+f"(d[37]), "+f"(d[38]), "+f"(d[39]), "+f"(d[40]), "+f"(d[41]), "+f"(d[42]), "+f"(d[43]), "+f"(d[44]), "+f"(d[45]), "+f"(d[46]), "+f"(d[47]), "+f"(d[48]), "+f"(d[49]), "+f"(d[50]), "+f"(d[51]), "+f"(d[52]), "+f"(d[53]), "+f"(d[54]), "+f"(d[55]), "+f"(d[56]), "+f"(d[57]), "+f"(d[58]), "+f"(d[59]), "+f"(d[60]), "+f"(d[61]), "+f"(d[62]), "+f"(d[63]), "+f"(d[64]), "+f"(d[65]), "+f"(d[66]), "+f"(d[67]), "+f"(d[68]), "+f"(d[69]), "+f"(d[70]), "+f"(d[71]), "+f"(d[72]), "+f"(d[73]), "+f"(d[74]), "+f"(d[75]), "+f"(d[76]), "+f"(d[77]), "+f"(d[78]), "+f"(d[79]), "+f"(d[80]), "+f"(d[81]), "+f"(d[82]), "+f"(d[83]), "+f"(d[84]), "+f"(d[85]), "+f"(d[86]), "+f"(d[87]), "+f"(d[88]), "+f"(d[89]), "+f"(d[90]), "+f"(d[91]), "+f"(d[92]), "+f"(d[93]), "+f"(d[94]), "+f"(d[95])
    : "r"(alo), "r"(blo), "r"(sd));
}
template <uint32_t BHI, int SD> __device__ __forceinline__ void wgmma_rs_n64(float (&d)[32], uint32_t a0, uint32_t a1, uint32_t a2, uint32_t a3, uint32_t blo) {
  asm volatile("{\n.reg .b64 db;\nmov.b64 db, {%36, %37};\n"
    "wgmma.mma_async.sync.aligned.m64n64k16.f32.bf16.bf16 {%0, %1, %2, %3, %4, %5, %6, %7, %8, %9, %10, %11, %12, %13, %14, %15, %16, %17, %18, %19, %20, %21, %22, %23, %24, %25, %26, %27, %28, %29, %30, %31}, {%32,%33,%34,%35}, db, %38, 1, 1, 0;\n}\n"
    : "+f"(d[0]), "+f"(d[1]), "+f"(d[2]), "+f"(d[3]), "+f"(d[4]), "+f"(d[5]), "+f"(d[6]), "+f"(d[7]), "+f"(d[8]), "+f"(d[9]), "+f"(d[10]), "+f"(d[11]), "+f"(d[12]), "+f"(d[13]), "+f"(d[14]), "+f"(d[15]), "+f"(d[16]), "+f"(d[17]), "+f"(d[18]), "+f"(d[19]), "+f"(d[20]), "+f"(d[21]), "+f"(d[22]), "+f"(d[23]), "+f"(d[24]), "+f"(d[25]), "+f"(d[26]), "+f"(d[27]), "+f"(d[28]), "+f"(d[29]), "+f"(d[30]), "+f"(d[31])
    : "r"(a0), "r"(a1), "r"(a2), "r"(a3), "r"(blo), "n"(BHI), "n"(SD));
}
template <uint32_t BHI, int SD> __device__ __forceinline__ void wgmma_rs_n24(float (&d)[12], uint32_t a0, uint32_t a1, uint32_t a2, uint32_t a3, uint32_t blo) {
  asm volatile("{\n.reg .b64 db;\nmov.b64 db, {%16, %17};\n"
    "wgmma.mma_async.sync.aligned.m64n24k16.f32.bf16.bf16 {%0, %1, %2, %3, %4, %5, %6, %7, %8, %9, %10, %11}, {%12,%13,%14,%15}, db, %18, 1, 1, 1;\n}\n"
    : "+f"(d[0]), "+f"(d[1]), "+f"(d[2]), "+f"(d[3]), "+f"(d[4]), "+f"(d[5]), "+f"(d[6]), "+f"(d[7]), "+f"(d[8]), "+f"(d[9]), "+f"(d[10]), "+f"(d[11])
    : "r"(a0), "r"(a1), "r"(a2), "r"(a3), "r"(blo), "n"(BHI), "n"(SD));
}

#define GP(...) __VA_ARGS__
#define HINT "20000"
namespace {

constexpr int SEQ = 2048, DM = 576, FF = 4608, HW = FF + DM;
constexpr int NCTA = 132, NATT = 128;
#define P_C1 26
#define P_C2 27
#define P_F 22
#define P_LATE 0
constexpr int LATE = P_LATE;
constexpr int NL = 8, C1 = P_C1, C2 = P_C2, CF = P_F;
constexpr int MAXSLOT = 160;
constexpr int GST = 4, GSTB = 40960;
constexpr int KST = 5, KSTB = 6144;
constexpr int QB = 128 * 36;
constexpr int OFF_STG = GST * GSTB;
constexpr int OFF_KV = OFF_STG + 32768;
constexpr int OFF_Q = OFF_KV + KST * KSTB;
constexpr int OFF_BAR = OFF_Q + QB;
constexpr int SMEM_BYTES = OFF_BAR + 512;
constexpr int BH = 16384, BH2 = 12288;
constexpr float MBIAS = 72.f;

constexpr int FL_LN = 0;
constexpr int FL_QKV = 512;
constexpr int FL_H = 1024;
constexpr int FL_P = FL_H + 16 * 96;
constexpr int FL_DONE = FL_P + MAXSLOT;
constexpr int FL_TOTAL = FL_DONE + 32;

struct Sched {
  uint8_t nseg, own, om, on, np, ps[3];
  uint8_t sm[4], sn[4], k0[4], k1[4], slot[4];
  uint8_t kc;
  uint8_t ne[4];
};
struct Params {
  CUtensorMap xn, H, out, wqkv, wg1, wu1, wg2, wu2, wd, wo, xin;
  const __nv_bfloat16* x;
  uint32_t zero, pad;
  Sched sch[NCTA];
};

__device__ __align__(1024) __nv_bfloat16 g_xn[SEQ * DM];
__device__ __align__(1024) __nv_bfloat16 g_H[SEQ * HW];
__device__ __align__(1024) uint8_t g_q[32 * SEQ * 36];
__device__ __align__(1024) uint8_t g_kv[32 * 32 * KSTB];
__device__ __align__(1024) uint4 g_part[MAXSLOT * 3072];
__device__ int g_flags[FL_TOTAL];
#define STAMP(i)
#define TIC(v)
#define TOC(acc, v)
#define PUT(i, val)

__device__ __forceinline__ void wg_fence() { asm volatile("wgmma.fence.sync.aligned;" ::: "memory"); }
__device__ __forceinline__ void wg_commit() { asm volatile("wgmma.commit_group.sync.aligned;" ::: "memory"); }
template <int N> __device__ __forceinline__ void wg_wait() { asm volatile("wgmma.wait_group.sync.aligned %0;" ::"n"(N) : "memory"); }
template <int N> __device__ __forceinline__ void pin(float (&d)[N]) {
#pragma unroll
  for (int i = 0; i < N; i++) asm volatile("" : "+f"(d[i])::"memory");
}
template <int N> __device__ __forceinline__ void pin(uint32_t (&d)[N]) {
#pragma unroll
  for (int i = 0; i < N; i++) asm volatile("" : "+r"(d[i])::"memory");
}
__device__ __forceinline__ uint32_t desc_lo(uint32_t addr, uint32_t lbo) { return ((addr & 0x3FFFF) >> 4) | ((lbo >> 4) << 16); }
__device__ __forceinline__ float ex2(float x) { float r; asm("ex2.approx.ftz.f32 %0, %1;" : "=f"(r) : "f"(x)); return r; }
__device__ __forceinline__ float tanhf_fast(float x) { float r; asm("tanh.approx.f32 %0, %1;" : "=f"(r) : "f"(x)); return r; }
__device__ __forceinline__ uint32_t pack2(float lo, float hi) { uint32_t r; asm("cvt.rn.bf16x2.f32 %0, %1, %2;" : "=r"(r) : "f"(hi), "f"(lo)); return r; }
__device__ __forceinline__ float bf_lo(uint32_t v) { float r; asm("shl.b32 %0, %1, 16;" : "=f"(r) : "r"(v)); return r; }
__device__ __forceinline__ float bf_hi(uint32_t v) { float r; asm("and.b32 %0, %1, 0xffff0000;" : "=f"(r) : "r"(v)); return r; }
__device__ __forceinline__ float bf_rn(float v) { return __bfloat162float(__float2bfloat16_rn(v)); }
__device__ __forceinline__ float fdiv(float a, float b) { float r; asm("div.full.f32 %0, %1, %2;" : "=f"(r) : "f"(a), "f"(b)); return r; }
__device__ __forceinline__ float fsqrt(float a) { float r; asm("sqrt.approx.f32 %0, %1;" : "=f"(r) : "f"(a)); return r; }
__device__ __forceinline__ int lane_id() { int l; asm volatile("mov.u32 %0, %%laneid;" : "=r"(l)); return l; }
__device__ __forceinline__ uint32_t clk32() { uint32_t c; asm volatile("mov.u32 %0, %%clock;" : "=r"(c)); return c; }

__device__ __forceinline__ void mbar_init(uint32_t a, uint32_t c) { asm volatile("mbarrier.init.shared::cta.b64 [%0], %1;" ::"r"(a), "r"(c) : "memory"); }
__device__ __forceinline__ void mbar_arrive(uint32_t a) { asm volatile("mbarrier.arrive.shared::cta.b64 _, [%0];" ::"r"(a) : "memory"); }
__device__ __forceinline__ bool mbar_test(uint32_t a, uint32_t ph) {
  uint32_t ok;
  asm volatile("{\n.reg .pred p;\nmbarrier.test_wait.parity.shared::cta.b64 p, [%1], %2;\nselp.u32 %0, 1, 0, p;\n}\n" : "=r"(ok) : "r"(a), "r"(ph) : "memory");
  return ok;
}
__device__ __forceinline__ void mbar_wait(uint32_t a, uint32_t ph) {
  asm volatile("{\n.reg .pred p;\n.reg .u32 n;\nmbarrier.try_wait.parity.shared::cta.b64 p, [%0], %1;\n@p bra D_%=;\nmov.u32 n, 0;\n"
               "W_%=:\nmbarrier.try_wait.parity.shared::cta.b64 p, [%0], %1, " HINT ";\n@p bra D_%=;\n"
               "add.u32 n, n, 1;\nsetp.lt.u32 p, n, 200000;\n@p bra W_%=;\ntrap;\nD_%=:\n}\n" ::"r"(a), "r"(ph) : "memory");
}
#define ELECT "{\n.reg .pred e;\nelect.sync _|e, 0xffffffff;\n@e "
__device__ __forceinline__ uint64_t policy_stream() {
  uint64_t p; asm("createpolicy.fractional.L2::evict_first.b64 %0, 1.0;" : "=l"(p)); return p;
}
__device__ __forceinline__ void expect1(uint32_t a, uint32_t b) { asm volatile(ELECT "mbarrier.arrive.expect_tx.shared::cta.b64 _, [%0], %1;\n}\n" ::"r"(a), "r"(b) : "memory"); }
__device__ __forceinline__ void arrive1(uint32_t a) { asm volatile(ELECT "mbarrier.arrive.shared::cta.b64 _, [%0];\n}\n" ::"r"(a) : "memory"); }
__device__ __forceinline__ void tma2d(uint32_t dst, const CUtensorMap* m, int c0, int c1, uint32_t bar) {
  asm volatile(ELECT "cp.async.bulk.tensor.2d.shared::cluster.global.mbarrier::complete_tx::bytes [%0], [%1, {%3, %4}], [%2];\n}\n"
               ::"r"(dst), "l"(m), "r"(bar), "r"(c0), "r"(c1) : "memory");
}
__device__ __forceinline__ void tma3d_mc(uint32_t dst, const CUtensorMap* m, int c0, int c1, int c2, uint32_t bar) {
  asm volatile(ELECT "cp.async.bulk.tensor.3d.shared::cluster.global.mbarrier::complete_tx::bytes.multicast::cluster [%0], [%1, {%3, %4, %5}], [%2], %6;\n}\n"
               ::"r"(dst), "l"(m), "r"(bar), "r"(c0), "r"(c1), "r"(c2), "h"((uint16_t)3) : "memory");
}
__device__ __forceinline__ void tma3d_mc_stream(uint32_t dst, const CUtensorMap* m, int c0, int c1, int c2, uint32_t bar, uint64_t pol) {
  asm volatile(ELECT "cp.async.bulk.tensor.3d.shared::cluster.global.mbarrier::complete_tx::bytes.multicast::cluster.L2::cache_hint [%0], [%1, {%3, %4, %5}], [%2], %6, %7;\n}\n"
               ::"r"(dst), "l"(m), "r"(bar), "r"(c0), "r"(c1), "r"(c2), "h"((uint16_t)3), "l"(pol) : "memory");
}
__device__ __forceinline__ void bulk_load(uint32_t dst, const void* src, uint32_t bytes, uint32_t bar, uint64_t pol) {
  asm volatile(ELECT "cp.async.bulk.shared::cluster.global.mbarrier::complete_tx::bytes.L2::cache_hint [%0], [%1], %2, [%3], %4;\n}\n"
               ::"r"(dst), "l"(src), "r"(bytes), "r"(bar), "l"(pol) : "memory");
}
__device__ __forceinline__ void bulk_load_mc(uint32_t dst, const void* src, uint32_t bytes, uint32_t bar, uint64_t pol) {
  asm volatile(ELECT "cp.async.bulk.shared::cluster.global.mbarrier::complete_tx::bytes.multicast::cluster.L2::cache_hint [%0], [%1], %2, [%3], %4, %5;\n}\n"
               ::"r"(dst), "l"(src), "r"(bytes), "r"(bar), "h"((uint16_t)3), "l"(pol) : "memory");
}
__device__ __forceinline__ uint32_t map_peer(uint32_t a, uint32_t rank) { uint32_t r; asm("mapa.shared::cluster.u32 %0, %1, %2;" : "=r"(r) : "r"(a), "r"(rank)); return r; }
__device__ __forceinline__ void arrive_cluster(uint32_t a) { asm volatile("mbarrier.arrive.relaxed.cluster.shared::cluster.b64 _, [%0];" ::"r"(a) : "memory"); }
__device__ __forceinline__ void arrive_cluster1(uint32_t a) { asm volatile(ELECT "mbarrier.arrive.relaxed.cluster.shared::cluster.b64 _, [%0];\n}\n" ::"r"(a) : "memory"); }
__device__ __forceinline__ void release_stage(uint32_t a, int lane) { if (lane < 2) arrive_cluster(map_peer(a, lane)); }
__device__ __forceinline__ void cluster_sync() { asm volatile("barrier.cluster.arrive.relaxed.aligned;\nbarrier.cluster.wait.aligned;" ::: "memory"); }
__device__ __forceinline__ int uni(int v) { return __shfl_sync(0xffffffffu, v, 0); }
__device__ __forceinline__ void tma2d_store(const CUtensorMap* m, int c0, int c1, uint32_t src) {
  asm volatile("cp.async.bulk.tensor.2d.global.shared::cta.bulk_group [%0, {%2, %3}], [%1];" ::"l"(m), "r"(src), "r"(c0), "r"(c1) : "memory");
}
__device__ __forceinline__ void pf3d(const CUtensorMap* m, int c0, int c1, int c2) {
  asm volatile("cp.async.bulk.prefetch.tensor.3d.L2.global [%0, {%1, %2, %3}];" ::"l"(m), "r"(c0), "r"(c1), "r"(c2) : "memory");
}
__device__ __forceinline__ void bulk_commit() { asm volatile("cp.async.bulk.commit_group;" ::: "memory"); }
__device__ __forceinline__ void bulk_wait0() { asm volatile("cp.async.bulk.wait_group 0;" ::: "memory"); }
__device__ __forceinline__ void fence_async_glob() { asm volatile("fence.proxy.async.global;" ::: "memory"); }
__device__ __forceinline__ void fence_cta() { asm volatile("fence.acq_rel.cta;" ::: "memory"); }
__device__ __forceinline__ void fence_release() { asm volatile("fence.release.gpu;" ::: "memory"); }
__device__ __forceinline__ void red_relaxed(int* p, int v = 1) { asm volatile("red.relaxed.gpu.global.add.s32 [%0], %1;" ::"l"(p), "r"(v) : "memory"); }
__device__ __forceinline__ void bar_arrive(int id, int n) { asm volatile("bar.arrive %0, %1;" ::"r"(id), "r"(n) : "memory"); }
__device__ __forceinline__ void bar_sync(int id, int n) { asm volatile("bar.sync %0, %1;" ::"r"(id), "r"(n) : "memory"); }
__device__ __forceinline__ void fence_async_smem() { asm volatile("fence.proxy.async.shared::cta;" ::: "memory"); }
__device__ __forceinline__ void red_release(int* p) { asm volatile("red.release.gpu.global.add.s32 [%0], 1;" ::"l"(p) : "memory"); }
__device__ __forceinline__ int ld_acquire(const int* p) { int v; asm volatile("ld.acquire.gpu.global.s32 %0, [%1];" : "=r"(v) : "l"(p) : "memory"); return v; }
__device__ __forceinline__ void stsm4(uint32_t a, uint32_t r0, uint32_t r1, uint32_t r2, uint32_t r3) {
  asm volatile("stmatrix.sync.aligned.m8n8.x4.shared.b16 [%0], {%1,%2,%3,%4};" ::"r"(a), "r"(r0), "r"(r1), "r"(r2), "r"(r3) : "memory");
}
__device__ __forceinline__ void ldsm4(uint32_t a, uint32_t& r0, uint32_t& r1, uint32_t& r2, uint32_t& r3) {
  asm volatile("ldmatrix.sync.aligned.m8n8.x4.shared.b16 {%0,%1,%2,%3}, [%4];" : "=r"(r0), "=r"(r1), "=r"(r2), "=r"(r3) : "r"(a) : "memory");
}
__device__ __forceinline__ uint32_t lds32(uint32_t a) { uint32_t v; asm volatile("ld.shared.u32 %0, [%1];" : "=r"(v) : "r"(a) : "memory"); return v; }
__device__ __forceinline__ uint4 lds128(uint32_t a) {
  uint4 v; asm volatile("ld.shared.v4.u32 {%0,%1,%2,%3}, [%4];" : "=r"(v.x), "=r"(v.y), "=r"(v.z), "=r"(v.w) : "r"(a) : "memory"); return v;
}
__device__ __forceinline__ void poll_ge(const int* p, int target) {
  const uint32_t t0 = clk32();
  while (!__all_sync(0xffffffffu, ld_acquire(p) >= target)) { __nanosleep(20); if (clk32() - t0 > 0x60000000u) __trap(); }
}

__device__ __forceinline__ uint32_t xn_off(int kb) { return kb == 0 ? OFF_KV : ((kb + 1) & 3) * GSTB + (kb > 4 ? 8192 : 0); }
__device__ __forceinline__ void layernorm_rows(uint4 (&v)[9], uint32_t sb, int r, int grow, bool to_global, int lane) {
  float f[72];
  float s = 0.f;
#pragma unroll
  for (int i = 0; i < 9; i++) {
    f[8 * i] = bf_lo(v[i].x); f[8 * i + 1] = bf_hi(v[i].x); f[8 * i + 2] = bf_lo(v[i].y); f[8 * i + 3] = bf_hi(v[i].y);
    f[8 * i + 4] = bf_lo(v[i].z); f[8 * i + 5] = bf_hi(v[i].z); f[8 * i + 6] = bf_lo(v[i].w); f[8 * i + 7] = bf_hi(v[i].w);
    s += ((f[8 * i] + f[8 * i + 1]) + (f[8 * i + 2] + f[8 * i + 3])) + ((f[8 * i + 4] + f[8 * i + 5]) + (f[8 * i + 6] + f[8 * i + 7]));
  }
#pragma unroll
  for (int o = 4; o; o >>= 1) s += __shfl_xor_sync(0xffffffffu, s, o);
  const float mean = s * (1.f / DM);
  float q0 = 0.f, q1 = 0.f;
#pragma unroll
  for (int i = 0; i < 72; i += 2) { const float a = f[i] - mean, b = f[i + 1] - mean; q0 = fmaf(a, a, q0); q1 = fmaf(b, b, q1); }
  float q = q0 + q1;
#pragma unroll
  for (int o = 4; o; o >>= 1) q += __shfl_xor_sync(0xffffffffu, q, o);
  const float mb = bf_rn(mean);
  const float inv = fdiv(1.f, bf_rn(fsqrt(bf_rn(bf_rn(q * (1.f / DM)) + 1e-5f))));
  auto nrm = [&](int i) { const uint32_t d = pack2(f[i] - mb, f[i + 1] - mb); return pack2(bf_lo(d) * inv, bf_hi(d) * inv); };
  auto halve = [](uint32_t v) { return pack2(bf_lo(v) * 0.5f, bf_hi(v) * 0.5f); };
  uint4* g = reinterpret_cast<uint4*>(g_xn + (size_t)grow * DM) + (lane & 7);
#pragma unroll
  for (int i = 0; i < 9; i++) {
    const uint4 o = make_uint4(nrm(8 * i), nrm(8 * i + 2), nrm(8 * i + 4), nrm(8 * i + 6));
    asm volatile("st.shared.v4.u32 [%0], {%1,%2,%3,%4};" ::"r"(sb + xn_off(i) + r * 128 + (((lane ^ r) & 7) << 4)), "r"(o.x), "r"(o.y), "r"(o.z), "r"(o.w) : "memory");
    if (to_global) g[8 * i] = make_uint4(halve(o.x), halve(o.y), halve(o.z), halve(o.w));
  }
  fence_async_smem();
}

__device__ __forceinline__ void attn_row_slow(int head, int row, int lane) {
  const uint8_t* qp = g_q + (size_t)head * (SEQ * 36) + row * 36;
  float q[18], o[18];
#pragma unroll
  for (int d = 0; d < 18; d += 2) {
    uint32_t v = *reinterpret_cast<const volatile uint32_t*>(qp + d * 2);
    q[d] = bf_lo(v); q[d + 1] = bf_hi(v); o[d] = 0.f; o[d + 1] = 0.f;
  }
  float m = -INFINITY, l = 0.f;
#pragma unroll 1
  for (int key = lane; key < SEQ; key += 32) {
    const uint8_t* kp = g_kv + (size_t)head * (32 * KSTB) + (key >> 6) * KSTB + ((key >> 3) & 7) * 384 + (key & 7) * 16;
    float s = 0.f;
#pragma unroll
    for (int d = 0; d < 18; d += 2) {
      uint32_t v = *reinterpret_cast<const volatile uint32_t*>(kp + (d >> 3) * 128 + (d & 7) * 2);
      s = fmaf(q[d], bf_lo(v), s); s = fmaf(q[d + 1], bf_hi(v), s);
    }
    const float mn = fmaxf(m, s), c = ex2(m - mn), p = ex2(s - mn);
    m = mn; l = l * c + p;
#pragma unroll
    for (int d = 0; d < 18; d += 2) {
      uint32_t v = *reinterpret_cast<const volatile uint32_t*>(kp + 3072 + (d >> 3) * 128 + (d & 7) * 2);
      o[d] = fmaf(p, bf_lo(v), o[d] * c); o[d + 1] = fmaf(p, bf_hi(v), o[d + 1] * c);
    }
  }
  float M = m;
#pragma unroll
  for (int t = 16; t; t >>= 1) M = fmaxf(M, __shfl_xor_sync(0xffffffffu, M, t));
  const float c = ex2(m - M);
  l *= c;
#pragma unroll
  for (int t = 16; t; t >>= 1) l += __shfl_xor_sync(0xffffffffu, l, t);
  uint32_t* dst = reinterpret_cast<uint32_t*>(g_H + (size_t)row * HW + FF + head * 18);
#pragma unroll
  for (int d = 0; d < 18; d += 2) {
    float a = o[d] * c, b = o[d + 1] * c;
#pragma unroll
    for (int t = 16; t; t >>= 1) { a += __shfl_xor_sync(0xffffffffu, a, t); b += __shfl_xor_sync(0xffffffffu, b, t); }
    if (lane == 0) dst[d >> 1] = pack2(fdiv(a, l), fdiv(b, l));
  }
}

constexpr uint32_t AB = (BH >> 4) + (255u << 16);
template <bool BOTH>
__device__ __forceinline__ void gemm_run(float (&a0)[96], float (&a1)[96], int nk, int keep, int& st, uint32_t& ph, uint32_t dA,
                                         uint32_t bar_full, int lane, uint32_t& gw) {
  uint32_t da = dA + st * (GSTB >> 4);
  uint32_t rel = 0;
  int kb = 0;
  pin(a0); pin(a1);
#pragma unroll 1
  do {
    wg_fence();
    const uint32_t aa = BOTH ? da : dA + (xn_off(kb) >> 4);
    wgmma_ss_n192(a0, aa, da + AB, kb | keep);
    wg_commit();
    wg_wait<1>();
    if (rel) release_stage(rel, lane);
    if (BOTH) {
      wgmma_ss_n192(a1, da + 512, da + AB, kb | keep);
      wg_commit();
      wg_wait<1>();
    }
    rel = bar_full + 32 + 8 * st;
    if (++st == GST) { st = 0; ph ^= 1; }
    bool ready = false;
#pragma unroll
    for (int k = 1; k < 4; k++) {
      if (k == 3) ready = mbar_test(bar_full + 8 * st, ph);
      wgmma_ss_n192(a0, aa + 2 * k, da + AB + (k >> 1) * (BH2 >> 4) + (k & 1) * 128, 1);
      wg_commit();
      if (BOTH) {
        wg_wait<1>();
        wgmma_ss_n192(a1, da + 512 + 2 * k, da + AB + (k >> 1) * (BH2 >> 4) + (k & 1) * 128, 1);
        wg_commit();
      }
      if (k < 3) wg_wait<1>();
    }
    da = dA + st * (GSTB >> 4);
    if (++kb < nk && !ready) { TIC(t0); mbar_wait(bar_full + 8 * st, ph); TOC(gw, t0); }
    wg_wait<1>();
  } while (kb < nk);
  wg_wait<0>();
  pin(a0); pin(a1);
  release_stage(rel, lane);
}

template <bool ODD>
__device__ __forceinline__ void glu_epilogue(const float (&E)[96], uint32_t s0) {
#pragma unroll
  for (int g = 0; g < 8; g += 2) {
    uint32_t h[4], w[4];
    if (ODD) ldsm4((s0 + 16384) ^ (g << 4), w[0], w[1], w[2], w[3]);
#pragma unroll
    for (int i = 0; i < 4; i++) {
      const int e = 4 * g + 2 * i;
      if (ODD) {
        h[i] = pack2(fmaf(tanhf_fast(E[64 + e]), E[32 + e], E[32 + e]), fmaf(tanhf_fast(E[65 + e]), E[33 + e], E[33 + e]));
        w[i] = pack2(bf_lo(w[i]) * E[e], bf_hi(w[i]) * E[e + 1]);
      } else {
        h[i] = pack2(fmaf(tanhf_fast(E[e]), E[64 + e], E[64 + e]), fmaf(tanhf_fast(E[e + 1]), E[65 + e], E[65 + e]));
        w[i] = pack2(tanhf_fast(E[32 + e]) + 1.f, tanhf_fast(E[33 + e]) + 1.f);
      }
    }
    stsm4(s0 ^ (g << 4), h[0], h[1], h[2], h[3]);
    stsm4((s0 + 16384) ^ (g << 4), w[0], w[1], w[2], w[3]);
  }
}

__device__ __forceinline__ void qkv_scatter(uint32_t tile, int rb, int a, int w, int hoff, int hstep, int lane) {
  const int r8 = lane >> 2, j = lane & 3;
  const int h0 = ((a * 64 * 3641) >> 16) + hoff;
  uint8_t* const qb = g_q + rb * 288 + lane * 4;
  uint8_t* const kb = g_kv + (rb >> 3) * KSTB + (rb & 7) * 384 + r8 * 16 + j * 4;
  const uint32_t row = tile + (w * 16 + r8) * 400 + 128;
#pragma unroll 1
  for (int h = h0; h * 18 < a * 64 + 64; h += hstep) {
    uint32_t v[3][4], q[5];
    bool data[3], qd[5];
    const int col0 = h * 18 - a * 64;
#pragma unroll
    for (int i = 0; i < 5; i++) {
      const int wd = lane + 32 * i, r = (wd * 57) >> 9, col = col0 + 2 * (wd - 9 * r);
      qd[i] = wd < 144 && (unsigned)col < 64u;
      q[i] = lds32(tile + (qd[i] ? (w * 16 + r) * 400 + col * 2 : 0));
    }
#pragma unroll
    for (int c = 0; c < 3; c++) {
      const int col = col0 + c * 8 + 2 * j;
      data[c] = (unsigned)col < 64u && (c < 2 || j == 0);
      const uint32_t src = row + (data[c] ? col : 0) * 2;
#pragma unroll
      for (int e = 0; e < 4; e++) v[c][e] = lds32(src + (e >> 1) * 128 + (e & 1) * 3200);
    }
    const bool pad = j > 0 && (unsigned)(col0 + 16) < 64u;
    if (j > 0) { v[2][0] = v[2][1] = j == 1 ? 0x3f803f80u : 0u; v[2][2] = v[2][3] = j == 1 ? 0x00003f80u : 0u; }
    uint8_t* const kp = kb + h * (32 * KSTB);
#pragma unroll
    for (int c = 0; c < 3; c++)
      if (data[c] || (c == 2 && pad)) {
        *reinterpret_cast<uint32_t*>(kp + c * 128) = v[c][0]; *reinterpret_cast<uint32_t*>(kp + c * 128 + 384) = v[c][1];
        *reinterpret_cast<uint32_t*>(kp + c * 128 + 3072) = v[c][2]; *reinterpret_cast<uint32_t*>(kp + c * 128 + 3456) = v[c][3];
      }
    uint8_t* const qp = qb + h * (SEQ * 36);
#pragma unroll
    for (int i = 0; i < 5; i++) if (qd[i]) *reinterpret_cast<uint32_t*>(qp + i * 128) = q[i];
  }
}

__global__ void __cluster_dims__(2, 1, 1) __launch_bounds__(512, 1) fused_kernel(const __grid_constant__ Params P) {
  extern __shared__ __align__(1024) uint8_t smem_raw[];
  const uint32_t sb = (uint32_t)__cvta_generic_to_shared(smem_raw);
  if (sb & 1023u) __trap();
  const uint32_t bar_gfull = sb + OFF_BAR, bar_gempty = bar_gfull + 32;
  const uint32_t bar_kfull = bar_gfull + 256, bar_kempty = bar_kfull + 80;
  const uint32_t bar_gdone = bar_gfull + 160, bar_gfree = bar_gfull + 168, bar_odone = bar_gfull + 176, bar_qdone = bar_gfull + 184, bar_xfree = bar_gfull + 200;
  const uint32_t bar_kpeer = bar_kfull + 160;
  const int tid = threadIdx.x;
  const int warp = __shfl_sync(0xffffffffu, tid >> 5, 0);
  const int wg = warp >> 2;
  const int cta = blockIdx.x;
  const bool att = cta < NATT;
  const int cm = cta & 15, cj = cta >> 4;
  const Sched& sch = P.sch[cta];
  const int nq = att ? 2 : 4, ngu = att ? 6 : 0;
  const int qa = att ? cta >> 5 : 8, qrow = att ? (cta & 31) * 64 : (cta - NATT) * 512;

  if (tid == 384) {
    for (int i = 0; i < GST; i++) { mbar_init(bar_gfull + 8 * i, 1); mbar_init(bar_gempty + 8 * i, 8); }
        for (int i = 0; i <= KST; i++) { mbar_init(bar_kfull + 8 * i, 1); mbar_init(bar_kempty + 8 * i, 8); }
    mbar_init(bar_gdone, 4); mbar_init(bar_gfree, 1); mbar_init(bar_odone, 8); mbar_init(bar_qdone, 8); mbar_init(bar_xfree, 4);
    for (int i = 0; i < KST; i++) mbar_init(bar_kpeer + 8 * i, 1);
    asm volatile("fence.mbarrier_init.release.cluster;" ::: "memory");
    fence_async_smem();
    STAMP(0);
  }
  uint4 xv[9];
  const int lrow = ((warp * 4 + (qa - 1) * 16) & 63) + ((tid & 31) >> 3);
  if (att) {
    const uint4* xr = reinterpret_cast<const uint4*>(P.x + (size_t)(qrow + lrow) * DM) + (tid & 7);
#pragma unroll
    for (int i = 0; i < 9; i++) xv[i] = __ldg(xr + 8 * i);
  }
  if (tid >= 480 && tid < 491) asm volatile("prefetch.tensormap [%0];" ::"l"(&P.xn + (tid - 480)) : "memory");
  __syncwarp();
  cluster_sync();
  if (warp == 0) STAMP(30);
  const int rank = cta & 1;
  if (warp == 12)
    for (int i = 0; i < GST; i++) {
      expect1(bar_gfull + 8 * i, att ? GSTB - BH : GSTB);
      tma3d_mc(sb + i * GSTB + BH + rank * BH2, &P.wqkv, qa * 64, i * 64 + rank * 32, 0, bar_gfull + 8 * i);
    }
  if (tid == 416 && cm < 10) pf3d(&P.wqkv, qa * 64, GST * 64 + cm * 32, 0);
  if (tid == 448 && att && (cta & 31) < 18) pf3d(&P.wqkv, (qa + 4) * 64, (cta & 31) * 32, 0);
  __syncwarp();
  if (att) {
    layernorm_rows(xv, sb, lrow, qrow + lrow, wg == 1, tid & 31);
    if (warp == 0) STAMP(38);
    if (wg == 0) bar_sync(4, 512); else bar_arrive(4, 512);
    if (warp == 0) STAMP(39);
    if (wg == 1) {
      fence_async_glob();
      __syncwarp();
      if ((tid & 31) == 0) { fence_release(); red_relaxed(g_flags + FL_LN + (qrow >> 7) * 32, 4); }
    }
  }

  if (wg == 3) {
    asm volatile("setmaxnreg.dec.sync.aligned.u32 24;");
    const int pw = warp & 3, lane = lane_id();
    const bool el = lane == 0;
    if (pw == 0) {
      int st = 0; uint32_t ph = 1;
      const uint64_t pol = policy_stream();
      auto acquire = [&](uint32_t bytes) -> uint32_t {
        mbar_wait(bar_gempty + 8 * st, ph);
        expect1(bar_gfull + 8 * st, bytes);
        return sb + st * GSTB;
      };
      auto advance = [&]() { if (++st == GST) { st = 0; ph ^= 1; } };
      if (att) {
        ph ^= 1;
#pragma unroll 1
        for (int i = GST; i < 18; i++) {
          const uint32_t s = acquire(GSTB - BH);
          tma3d_mc(s + BH + rank * BH2, &P.wqkv, (i < 9 ? qa : qa + 4) * 64, (i < 9 ? i : i - 9) * 64 + rank * 32, 0, bar_gfull + 8 * st);
          advance();
        }
      } else {
#pragma unroll 1
        for (int t = 0; t < 4; t++) {
          const int row = uni(qrow + t * 128);
          int kb = 0;
          poll_ge(g_flags + FL_LN + (row >> 7) * 32, 128);
          fence_async_glob();
          if (t == 0) {
            STAMP(1);
            for (int i = 0; i < GST; i++) tma2d(sb + i * GSTB, &P.xn, i * 64, row, bar_gfull + 8 * i);
            kb = GST; ph ^= 1;
          }
          st = uni(st); ph = uni(ph); kb = uni(kb);
#pragma unroll 1
          for (; kb < 9; kb++) {
            const uint32_t s = acquire(GSTB);
            tma2d(s, &P.xn, kb * 64, row, bar_gfull + 8 * st);
            tma3d_mc(s + BH + rank * BH2, &P.wqkv, 8 * 64, kb * 64 + rank * 32, 0, bar_gfull + 8 * st);
            advance();
          }
        }
      }
      if (att) { poll_ge(g_flags + FL_LN + cm * 32, 128); fence_async_glob(); }
#pragma unroll 1
      for (int t = 0; t < ngu; t++) {
        const int a0 = uni((cj + 8 * (t >> 1)) * 3), hf = uni(t & 1);
        const CUtensorMap* m2 = hf ? &P.wu2 : &P.wg2; const CUtensorMap* m1 = hf ? &P.wg1 : &P.wu1;
        const int x2 = a0 + hf, x1 = a0 + 2 * hf;
        if (hf && t < 5 && lane < 7) {
          const int b = cm + 16 * lane;
          if (b < 108) pf3d(b < 54 ? &P.wg1 : &P.wu1, 0, ((b % 54) / 3) * 32, a0 + 24 + b % 3);
        }
        if (t == 2 && lane < 4) {
          const int b = cta + 128 * lane;
          if (b < 432) pf3d(&P.wd, 0, (b / 3) * 32, (b % 3) * 3);
          else if (b < 486) pf3d(&P.wo, 0, ((b - 432) / 3) * 32, ((b - 432) % 3) * 3);
        }
        st = uni(st); ph = uni(ph);
#pragma unroll 1
        for (int kb = 0; kb < 9; kb++) {
          const uint32_t s = acquire(GSTB), b = bar_gfull + 8 * st;
          tma2d(s, &P.xn, kb * 64, cm * 128, b);
          tma3d_mc_stream(s + BH + rank * BH2, m2, 0, kb * 64 + rank * 32, x2, b, pol);
          tma3d_mc_stream(s + BH + rank * BH2 + 8192, m1, 0, kb * 64 + rank * 32, x1, b, pol);
          advance();
        }
      }
      auto wait_h = [&](int m, int kb, int k1) -> int {
        const uint32_t t0 = clk32();
        const int i = kb + lane;
        uint32_t b;
        while (true) {
          bool ok = false;
          if (i < k1) ok = ld_acquire(g_flags + FL_H + m * 96 + i) >= (i < 72 ? 1 : 32 + 8 * (i & 1));
          b = __ballot_sync(0xffffffffu, ok);
          if (b & 1) break;
          __nanosleep(kb >= 76 ? 50 : 200);
          if (clk32() - t0 > 0x60000000u) __trap();
        }
        fence_async_glob();
        return uni(kb + (b == 0xffffffffu ? 32 : __ffs(~b) - 1));
      };
      auto down_range = [&](int m, int n, int k0, int k1) {
#pragma unroll 1
        for (int kb = k0; kb < k1;) {
          const int ready = wait_h(m, kb, k1);
          st = uni(st); ph = uni(ph); kb = uni(kb); m = uni(m); n = uni(n);
          const CUtensorMap* mw = kb < 72 ? &P.wd : &P.wo;
          const int y0 = rank * 32 - (kb < 72 ? 0 : 72 * 64);
#pragma unroll 1
          for (; kb < ready; kb++) {
            const uint32_t s = acquire(GSTB), b = bar_gfull + 8 * st;
            tma2d(s, &P.H, kb * 64, m * 128, b);
            tma3d_mc(s + BH + rank * BH2, mw, 0, kb * 64 + y0, n * 3, b);
            advance();
          }
        }
      };
#pragma unroll 1
      for (int i = 0; i < sch.nseg; i++) {
        const int va = sch.k0[i], vb = sch.k1[i], ne = sch.ne[i];
#pragma unroll 1
        for (int h = 0; h < 2; h++)
          down_range(sch.sm[i], sch.sn[i], h ? (va > ne ? va : ne) + 48 - ne : va, h ? vb + 48 - ne : (vb < ne ? vb : ne));
      }
      if (sch.own) {
        const int m = sch.om, n = sch.on;
        for (int c = 0; c < 2; c++) {
          const uint32_t s = acquire(c ? 16384 : 32768);
          tma2d(s, &P.xin, n * 192 + c * 128, m * 128, bar_gfull + 8 * st);
          if (!c) tma2d(s + 16384, &P.xin, n * 192 + 64, m * 128, bar_gfull + 8 * st);
          advance();
        }
#pragma unroll 1
        for (int h = 0; h < 4; h++) down_range(m, n, h == 0 ? 72 : h == 1 ? sch.kc - NL : h == 2 ? 48 + NL : 76, h == 0 ? 76 : h == 1 ? 48 : h == 2 ? 72 : 81 - LATE);
#pragma unroll 1
        for (int p = 0; p < sch.np; p++) {
          const int slot = sch.ps[p];
          poll_ge(g_flags + FL_P + slot, 1);
          fence_async_glob();
          for (int c = 0; c < 2; c++) {
            const uint32_t s = acquire(24576);
            bulk_load(s, g_part + slot * 3072 + c * 1536, 24576, bar_gfull + 8 * st, pol);
            advance();
          }
        }
        down_range(m, n, 81 - LATE, 81);
      }
    } else if (pw == 1) {
      if (att) {
        const uint64_t pol = policy_stream();
        const uint32_t peer = map_peer(bar_kpeer, rank ^ 1);
        uint32_t st = 0, ph = 0;
        int m = 0;
#pragma unroll 1
        for (int r = 0; r < 5; r++) {
          if (r < 4) {
            const int head = r * 8 + cj, atom = (head * 18 + (lane & 1) * 17) >> 6;
            poll_ge(g_flags + FL_QKV + atom * 32, atom < 8 ? 256 : 128);
            fence_async_glob();
            mbar_wait(bar_kempty + 8 * KST, (r & 1) ^ 1);
            expect1(bar_kfull + 8 * KST, QB);
            bulk_load(sb + OFF_Q, g_q + head * (SEQ * 36) + cm * QB, QB, bar_kfull + 8 * KST, pol);
            if (r == 0) STAMP(2);
          }
          if (r == 0) mbar_wait(bar_xfree, 0);
          const int mend = uni(r < 3 ? r * 32 + 27 : (r == 3 ? 0 : 129));
          st = uni(st); ph = uni(ph); m = uni(m);
#pragma unroll 1
          for (; m < mend; m++) {
            const int n = m - rank;
            mbar_wait(bar_kempty + 8 * st, ph ^ 1);
            arrive_cluster1(peer + 8 * st);
            expect1(bar_kfull + 8 * st, (unsigned)(m - 1) < 127u ? KSTB : 3072);
            mbar_wait(bar_kpeer + 8 * st, ph);
            if ((unsigned)n < 128u)
              bulk_load_mc(sb + OFF_KV + st * KSTB + rank * 3072, g_kv + (uint32_t)((((n >> 5) * 8 + cj) * 32 + (n & 31)) * KSTB + rank * 3072), 3072,
                           bar_kfull + 8 * st, pol);
            if (++st == KST) { st = 0; ph ^= 1; }
          }
        }
      }
    } else if (pw == 2) {
      if (att) {
        mbar_wait(bar_qdone, 0);
        mbar_wait(bar_qdone, 1);
        if (el) { fence_async_glob(); fence_release(); red_relaxed(g_flags + FL_QKV + (qa + 4) * 32, 8); }
        __syncwarp();
      }
      const int nt = ngu + sch.nseg;
#pragma unroll 1
      for (int u = 0; u < nt; u++) {
        mbar_wait(bar_gdone, u & 1);
        if (el) {
          if (u < ngu) {
            const int a0 = (cj + 8 * (u >> 1)) * 3;
            if (u & 1) { tma2d_store(&P.H, (a0 + 1) * 64, cm * 128, sb + OFF_STG + 16384); tma2d_store(&P.H, (a0 + 2) * 64, cm * 128, sb + OFF_STG); }
            else tma2d_store(&P.H, a0 * 64, cm * 128, sb + OFF_STG);
            bulk_commit(); bulk_wait0();
            fence_release();
            if (u & 1) { red_relaxed(g_flags + FL_H + cm * 96 + a0 + 1); red_relaxed(g_flags + FL_H + cm * 96 + a0 + 2); }
            else red_relaxed(g_flags + FL_H + cm * 96 + a0);
          } else {
            fence_async_glob();
            red_release(g_flags + FL_P + sch.slot[u - ngu]);
          }
          mbar_arrive(bar_gfree);
          if (u == ngu - 1) STAMP(35);
          if (u == nt - 1) STAMP(36);
        }
        __syncwarp();
      }
    } else {
      if (att) {
        if (lane < 7) {
          const int b = cm + 16 * lane;
          if (b < 108) pf3d(b < 54 ? &P.wg1 : &P.wu1, 0, ((b % 54) / 3) * 32, cj * 3 + b % 3);
        }
        for (int r = 0; r < 3; r++) {
          mbar_wait(bar_odone, r & 1);
          if (el) {
            const int head = r * 8 + cj, a0 = (head * 18) >> 6, a1 = (head * 18 + 17) >> 6;
            fence_async_glob();
            fence_release();
            red_relaxed(g_flags + FL_H + cm * 96 + 72 + a0, 8);
            if (a1 != a0) red_relaxed(g_flags + FL_H + cm * 96 + 72 + a1, 8);
          }
          __syncwarp();
        }
      }
    }
    if (pw == 0 || (pw == 1 && att)) {
      int old = 0;
      if (el) { __threadfence(); old = atomicAdd(g_flags + FL_DONE, 1); __threadfence(); }
      old = __shfl_sync(0xffffffffu, old, 0);
      if (old == NCTA + NATT - 1) for (int i = lane; i < FL_TOTAL; i += 32) g_flags[i] = 0;
    }
  } else if (wg >= 1) {
    const int lane = lane_id();
#pragma unroll 1
    for (int t = 0; t < nq; t++) {
      bar_sync(1, 384);
      if (att) qkv_scatter(sb + OFF_STG, (qrow >> 3) + (warp & 3) * 2, qa + 4 * t, warp & 3, wg - 1, 2, lane);
      else qkv_scatter(sb + OFF_STG, (qrow >> 3) + t * 16 + (warp - 4) * 2, 8, warp - 4, 0, 1, lane);
      fence_cta();
      __syncwarp();
      if (lane == 0) {
        mbar_arrive(bar_qdone);
        if (!att || !t) { fence_async_glob(); red_release(g_flags + FL_QKV + qa * 32); }
      }
      if (warp == 4) STAMP(t ? 34 : 32);
    }
    if (att) {
      const int wa = warp - 4;
      const int r8 = lane >> 2, j = lane & 3;
      const uint32_t kvd = __shfl_sync(0xffffffffu, desc_lo(sb + OFF_KV, 0), 0);
      const uint32_t kb0 = __shfl_sync(0xffffffffu, bar_kfull, 0);
      constexpr uint32_t DK = 8u << 16, DK2 = 16, DV = (24u << 16) + 192;
      const uint32_t qa = sb + OFF_Q + (wa * 16 + r8) * 36 + j * 4;
      uint32_t q[8], p[16];
      float s[32], s2[32], o[12];
      auto load_q = [&](int r) {
        mbar_wait(kb0 + 8 * KST, r & 1);
        q[0] = lds32(qa); q[1] = lds32(qa + 288); q[2] = lds32(qa + 16); q[3] = lds32(qa + 304);
        q[4] = j == 0 ? lds32(qa + 32) : 0u; q[5] = j == 0 ? lds32(qa + 320) : 0u; q[6] = 0u; q[7] = 0u;
      };
      load_q(0);
      mbar_wait(kb0, 0);
      pin(q);
      wg_fence();
      wgmma_rs_n64<24, 0>(s, q[0], q[1], q[2], q[3], kvd + DK);
      wgmma_rs_n64<24, 1>(s, q[4], q[5], q[6], q[7], kvd + DK2);
      wg_commit();
      mbar_wait(kb0 + 8, 0);
      wg_wait<0>();
      pin(s);
#pragma unroll
      for (int i = 0; i < 32; i++) s2[i] = 0.f;
#pragma unroll
      for (int i = 0; i < 16; i++) p[i] = 0u;
      uint32_t cur = uni(1), prev = uni(0), nph = uni(0);
      auto step = [&](float (&a)[32], float (&b)[32], int special) {
        const uint32_t d = kvd + cur * (KSTB >> 4);
        const uint32_t nxt = cur + 1 == KST ? 0 : cur + 1;
        nph ^= nxt == 0;
        pin(b); pin(q);
        wg_fence();
        wgmma_rs_n64<24, 0>(b, q[0], q[1], q[2], q[3], d + DK);
        wgmma_rs_n64<24, 1>(b, q[4], q[5], q[6], q[7], d + DK2);
        wg_commit();
#pragma unroll
        for (int i = 0; i < 32; i++) a[i] = ex2(a[i]);
        pin(a);
        wg_wait<1>();
        pin(p); pin(o);
        arrive1(kb0 + 80 + 8 * prev);
        const bool ready = mbar_test(kb0 + 8 * nxt, nph);
#pragma unroll
        for (int i = 0; i < 16; i++) p[i] = pack2(a[2 * i], a[2 * i + 1]);
        pin(p);
        wg_fence();
#pragma unroll
        for (int k = 0; k < 4; k++)
          wgmma_rs_n24<8, 1>(o, p[4 * k], p[4 * k + 1], p[4 * k + 2], p[4 * k + 3], d + DV + k * 48);
        wg_commit();
        if (!ready && special < 4) mbar_wait(kb0 + 8 * nxt, nph);
        wg_wait<1>();
        pin(b);
        prev = cur; cur = nxt;
      };
      auto new_rows = [&]() {
        if (lane == 0) mbar_arrive(kb0 + 80 + 8 * KST);
        {
          float m0 = fmaxf(s[0], s[1]), m1 = fmaxf(s[2], s[3]);
#pragma unroll
          for (int i = 4; i < 32; i += 4) { m0 = fmaxf(m0, fmaxf(s[i], s[i + 1])); m1 = fmaxf(m1, fmaxf(s[i + 2], s[i + 3])); }
          m0 = fmaxf(m0, __shfl_xor_sync(0xffffffffu, m0, 1)); m1 = fmaxf(m1, __shfl_xor_sync(0xffffffffu, m1, 1));
          m0 = fmaxf(m0, __shfl_xor_sync(0xffffffffu, m0, 2)); m1 = fmaxf(m1, __shfl_xor_sync(0xffffffffu, m1, 2));
          m0 = -(m0 + MBIAS); m1 = -(m1 + MBIAS);
          const float h0 = bf_rn(m0), h1 = bf_rn(m1), l0 = bf_rn(m0 - h0), l1 = bf_rn(m1 - h1);
          if (j == 1) { q[4] = pack2(h0, l0); q[5] = pack2(h1, l1); }
          m0 = h0 + l0; m1 = h1 + l1;
#pragma unroll
          for (int i = 0; i < 32; i += 4) { s[i] += m0; s[i + 1] += m0; s[i + 2] += m1; s[i + 3] += m1; }
        }
      };
      new_rows();
#pragma unroll 1
      for (int r = 0; r < 4; r++) {
        const int head = r * 8 + cj;
        TIC(tb);
#pragma unroll
        for (int i = 0; i < 12; i++) o[i] = 0.f;
        TOC(aw, tb);
        const int nq1 = uni(r < 3 ? 15 : -1), nl = uni(r == 3 ? 15 : -1);
        nph = uni(nph);
#pragma unroll 1
        for (int n = uni(0); n < 16; n++) {
          step(s, s2, 0);
          if (n == nq1) load_q(r + 1);
          step(s2, s, n == nl ? 4 : 0);
        }
        if (r < 3) new_rows();
        wg_wait<0>();
        pin(o); pin(s);
        TIC(te);
        const float l0 = __shfl_sync(0xffffffffu, o[8], (lane & ~3) | 1), l1 = __shfl_sync(0xffffffffu, o[10], (lane & ~3) | 1);
        float lo0 = fminf(fminf(fabsf(o[0]), fabsf(o[1])), fminf(fabsf(o[4]), fabsf(o[5])));
        float lo1 = fminf(fminf(fabsf(o[2]), fabsf(o[3])), fminf(fabsf(o[6]), fabsf(o[7])));
        float z0 = (o[0] + o[1] + o[4] + o[5]) * 0.f, z1 = (o[2] + o[3] + o[6] + o[7]) * 0.f;
        if (j == 0) {
          lo0 = fminf(lo0, fminf(fabsf(o[8]), fabsf(o[9]))); lo1 = fminf(lo1, fminf(fabsf(o[10]), fabsf(o[11])));
          z0 += (o[8] + o[9]) * 0.f; z1 += (o[10] + o[11]) * 0.f;
        }
        const bool ok0 = l0 >= 0x1p-90f && l0 <= 0x1p125f && lo0 >= l0 * 0x1p-33f && z0 == 0.f;
        const bool ok1 = l1 >= 0x1p-90f && l1 <= 0x1p125f && lo1 >= l1 * 0x1p-33f && z1 == 0.f;
        const int row = cm * 128 + wa * 16 + r8;
        {
          const float i0 = fdiv(1.f, l0), i1 = fdiv(1.f, l1);
          uint32_t* d0 = reinterpret_cast<uint32_t*>(g_H + (size_t)row * HW + FF + head * 18) + j;
          uint32_t* d1 = d0 + 8 * (HW / 2);
          d0[0] = pack2(o[0] * i0, o[1] * i0); d0[4] = pack2(o[4] * i0, o[5] * i0);
          d1[0] = pack2(o[2] * i1, o[3] * i1); d1[4] = pack2(o[6] * i1, o[7] * i1);
          if (j == 0) { d0[8] = pack2(o[8] * i0, o[9] * i0); d1[8] = pack2(o[10] * i1, o[11] * i1); }
        }
        const uint32_t bad0 = __ballot_sync(0xffffffffu, !ok0), bad1 = __ballot_sync(0xffffffffu, !ok1);
        if (bad0 | bad1) {
          __syncwarp();
#pragma unroll 1
          for (int rr = 0; rr < 16; rr++)
            if (((rr < 8 ? bad0 : bad1) >> ((rr & 7) * 4)) & 15u) attn_row_slow(head, cm * 128 + wa * 16 + rr, lane);
        }
        if (r < 3) {
          fence_cta();
          __syncwarp();
          if (lane == 0) mbar_arrive(bar_odone);
        } else {
          fence_async_glob();
          __syncwarp();
          if (lane == 0) {
            const int a0 = (head * 18) >> 6, a1 = (head * 18 + 17) >> 6;
            fence_release();
            red_relaxed(g_flags + FL_H + cm * 96 + 72 + a0);
            if (a1 != a0) red_relaxed(g_flags + FL_H + cm * 96 + 72 + a1);
          }
        }
        TOC(aw, te);
        if (wa == 0) { STAMP(4 + r); PUT(56, aw); PUT(57, am); PUT(59, nr); PUT(60 + r, ak); }
        if (wa == 4) { PUT(24 + r, clk32() - c0); PUT(28, nr); PUT(58, clk32() - c0); }
      }
    }
  } else {
    asm volatile("setmaxnreg.inc.sync.aligned.u32 232;");
    const int lane = lane_id();
    float acc0[96], acc1[96];
#pragma unroll
    for (int i = 0; i < 96; i++) { acc0[i] = 0.f; acc1[i] = 0.f; }
    int st = 0; uint32_t ph = 0;
    const uint32_t dA = __shfl_sync(0xffffffffu, desc_lo(sb, 16), 0);
    const uint32_t soff = (warp * 16 + (lane & 15)) * 128 + (((lane >> 4) ^ (lane & 7)) << 4);
    const int ntask = nq + sch.nseg + sch.own;
    uint32_t gw = 0;
#pragma unroll 1
    for (int t = 0; t < ntask; t++) {
      if (t == nq && ngu) {
#pragma unroll 1
        for (int u = 0; u < 6; u++) {
          mbar_wait(bar_gfull + 8 * st, ph);
          gemm_run<true>(acc0, acc1, 9, 0, st, ph, dA, bar_gfull, lane, gw);
          GP(if (warp == 0) STAMP(10 + 2 * u);)
          if (u) mbar_wait(bar_gfree, (u - 1) & 1); else mbar_wait(bar_qdone, 1);
          const uint32_t s4 = sb + OFF_STG + soff;
          if (u & 1) { glu_epilogue<true>(acc0, s4); glu_epilogue<true>(acc1, s4 + 8192); }
          else { glu_epilogue<false>(acc0, s4); glu_epilogue<false>(acc1, s4 + 8192); }
          fence_async_smem();
          __syncwarp();
          if (lane == 0) mbar_arrive(bar_gdone);
          GP(if (warp == 0) STAMP(11 + 2 * u);)
        }
      }
      const int sg = t - nq, u = sg < 0 ? sg : sg + ngu;
      const bool is_own = sg == sch.nseg;
      int nk = 9;
      if (sg >= 0) nk = is_own ? 81 - LATE - sch.kc : sch.k1[sg] - sch.k0[sg];
      if (is_own) {
#pragma unroll
        for (int c = 0; c < 2; c++) {
          mbar_wait(bar_gfull + 8 * st, ph);
          uint32_t dep = 0;
          auto ldx = [&](float (&acc)[96], uint32_t base) {
#pragma unroll
            for (int g = c * 16; g < (c ? 24 : 16); g += 2) {
              uint32_t w[4];
              ldsm4((base + ((g >> 3) & 1) * 16384) ^ ((g & 7) << 4), w[0], w[1], w[2], w[3]);
              dep |= w[3];
#pragma unroll
              for (int i = 0; i < 4; i++) { acc[4 * g + 2 * i] = bf_lo(w[i]); acc[4 * g + 2 * i + 1] = bf_hi(w[i]); }
            }
          };
          ldx(acc0, sb + st * GSTB + soff); ldx(acc1, sb + st * GSTB + soff + 8192);
          release_stage(bar_gempty + 8 * st + (dep & P.zero), lane);
          if (++st == GST) { st = 0; ph ^= 1; }
        }
      }
      { TIC(t0); mbar_wait(bar_gfull + 8 * st, ph); TOC(gw, t0); }
      if (att && t < 2) gemm_run<false>(acc0, acc1, nk, 0, st, ph, dA, bar_gfull, lane, gw);
      else gemm_run<true>(acc0, acc1, nk, is_own, st, ph, dA, bar_gfull, lane, gw);
      if (att && t == 1 && lane == 0) mbar_arrive(bar_xfree);
      GP(if (warp == 0) { STAMP(8 + 2 * (u < 0 ? 0 : u + 1)); PUT(44 + (u < 0 ? 0 : u + 1), gw); })
      if (is_own) {
#pragma unroll 1
        for (int pp = 0; pp < sch.np; pp++) {
          auto add = [&](float (&acc)[96]) {
            mbar_wait(bar_gfull + 8 * st, ph);
            const uint32_t a = sb + st * GSTB + (warp * 32 + lane) * 16;
            uint32_t dep = 0;
#pragma unroll
            for (int i = 0; i < 12; i++) {
              const uint4 v = lds128(a + i * 2048);
              dep |= v.w;
              acc[8 * i] += bf_lo(v.x); acc[8 * i + 1] += bf_hi(v.x); acc[8 * i + 2] += bf_lo(v.y); acc[8 * i + 3] += bf_hi(v.y);
              acc[8 * i + 4] += bf_lo(v.z); acc[8 * i + 5] += bf_hi(v.z); acc[8 * i + 6] += bf_lo(v.w); acc[8 * i + 7] += bf_hi(v.w);
            }
            release_stage(bar_gempty + 8 * st + (dep & P.zero), lane);
            if (++st == GST) { st = 0; ph ^= 1; }
          };
          add(acc0); add(acc1);
        }
        GP(if (warp == 0) STAMP(40);)
        mbar_wait(bar_gfree, (u - 1) & 1);
        if (LATE) {
          mbar_wait(bar_gfull + 8 * st, ph);
          gemm_run<true>(acc0, acc1, LATE, 1, st, ph, dA, bar_gfull, lane, gw);
        }
        GP(if (warp == 0) STAMP(41);)
#pragma unroll
        for (int a = 0; a < 3; a++) {
          auto st_out = [&](float (&acc)[96], uint32_t base) {
#pragma unroll
            for (int g = 8 * a; g < 8 * a + 8; g += 2)
              stsm4(base ^ ((g & 7) << 4), pack2(acc[4 * g], acc[4 * g + 1]), pack2(acc[4 * g + 2], acc[4 * g + 3]),
                    pack2(acc[4 * g + 4], acc[4 * g + 5]), pack2(acc[4 * g + 6], acc[4 * g + 7]));
          };
          const uint32_t buf = a < 2 ? sb + OFF_STG + a * 16384 : sb;
          st_out(acc0, buf + soff); st_out(acc1, buf + soff + 8192);
          fence_async_smem();
          bar_sync(12, 128);
          if (warp == 0 && lane == 0) tma2d_store(&P.out, sch.on * 192 + a * 64, sch.om * 128, buf);
        }
        if (warp == 0 && lane == 0) { bulk_commit(); bulk_wait0(); }
        if (warp == 0) STAMP(42);
        break;
      }
      if (u < 0) { if (t > 0) mbar_wait(bar_qdone, (t - 1) & 1); }
      else if (u > 0) mbar_wait(bar_gfree, (u - 1) & 1);
      if (u < 0) {
        const float qs = 0.23570226039551584f * 1.4426950408889634f;
        const float xs = att ? 1.f : 2.f;
        auto st_qkv = [&](float (&acc)[96], uint32_t pa) {
#pragma unroll
          for (int g = 0; g < 24; g += 2) {
            const float f = g < 8 ? qs * xs : xs;
            stsm4(pa + g * 16, pack2(acc[4 * g] * f, acc[4 * g + 1] * f), pack2(acc[4 * g + 2] * f, acc[4 * g + 3] * f),
                  pack2(acc[4 * g + 4] * f, acc[4 * g + 5] * f), pack2(acc[4 * g + 6] * f, acc[4 * g + 7] * f));
          }
        };
        const uint32_t pa = sb + OFF_STG + (warp * 16 + (lane & 15)) * 400 + (lane >> 4) * 16;
        st_qkv(acc0, pa);
        if (!att) st_qkv(acc1, pa + 64 * 400);
        bar_arrive(1, 384);
      } else {
        {
          uint4* pp = g_part + sch.slot[sg] * 3072 + warp * 32 + lane;
#pragma unroll
          for (int i = 0; i < 12; i++) {
            pp[i * 128] = make_uint4(pack2(acc0[8 * i], acc0[8 * i + 1]), pack2(acc0[8 * i + 2], acc0[8 * i + 3]),
                                     pack2(acc0[8 * i + 4], acc0[8 * i + 5]), pack2(acc0[8 * i + 6], acc0[8 * i + 7]));
            pp[i * 128 + 1536] = make_uint4(pack2(acc1[8 * i], acc1[8 * i + 1]), pack2(acc1[8 * i + 2], acc1[8 * i + 3]),
                                            pack2(acc1[8 * i + 4], acc1[8 * i + 5]), pack2(acc1[8 * i + 6], acc1[8 * i + 7]));
          }
          fence_cta();
        }
        __syncwarp();
        if (lane == 0) mbar_arrive(bar_gdone);
      }
      GP(if (warp == 0) { STAMP(9 + 2 * (u < 0 ? 0 : u + 1)); if (t == 0) STAMP(33); })
    }
  }
  __syncwarp();
  cluster_sync();
}

typedef CUresult (*EncodeFn)(CUtensorMap*, CUtensorMapDataType, cuuint32_t, void*, const cuuint64_t*, const cuuint64_t*, const cuuint32_t*,
                             const cuuint32_t*, CUtensorMapInterleave, CUtensorMapSwizzle, CUtensorMapL2promotion, CUtensorMapFloatOOBfill);

void make_map(EncodeFn enc, CUtensorMap* m, const void* ptr, int rank, uint64_t d0, uint64_t d1, uint64_t d2, uint64_t s1, uint64_t s2,
              uint32_t b0, uint32_t b1, uint32_t b2) {
  cuuint64_t gd[3] = {d0, d1, d2}, gs[2] = {s1, s2};
  cuuint32_t bd[3] = {b0, b1, b2}, es[3] = {1, 1, 1};
  enc(m, CU_TENSOR_MAP_DATA_TYPE_BFLOAT16, rank, const_cast<void*>(ptr), gd, gs, bd, es, CU_TENSOR_MAP_INTERLEAVE_NONE,
      CU_TENSOR_MAP_SWIZZLE_128B, CU_TENSOR_MAP_L2_PROMOTION_L2_256B, CU_TENSOR_MAP_FLOAT_OOB_FILL_NONE);
}

void build_schedule(Sched* s) {
  for (int i = 0; i < NCTA; i++) s[i] = Sched{};
  int nslot = 0;
  auto add = [&](int pair, int tp, int k0, int k1, int kc) {
    for (int r = 0; r < 2; r++) {
      Sched& c = s[2 * pair + r];
      c.sm[c.nseg] = 2 * (tp / 3) + r; c.sn[c.nseg] = tp % 3; c.k0[c.nseg] = k0; c.k1[c.nseg] = k1; c.ne[c.nseg] = kc - NL;
      c.slot[c.nseg] = nslot; c.nseg++;
      Sched& o = s[2 * tp + r];
      o.ps[o.np++] = nslot++; o.kc = kc;
    }
  };
  for (int t = 0; t < 48; t++) { s[t].own = 1; s[t].om = 2 * (t / 6) + (t & 1); s[t].on = (t / 2) % 3; }
  for (int t = 0; t < 8; t++) {
    add(64 + t / 4, t, 0, CF, CF + C2);
    add(24 + t, t, CF, CF + C2, CF + C2);
  }
  for (int t = 8; t < 24; t++) {
    add(32 + 2 * (t - 8), t, 0, C1, 2 * C1);
    add(33 + 2 * (t - 8), t, C1, 2 * C1, 2 * C1);
  }
}

}

extern "C" void kernel_launch(void* const* d_in, const int* in_sizes, int n_in, void* d_out, int out_size) {
  static EncodeFn enc = nullptr;
  if (!enc) {
    void* f = nullptr; cudaDriverEntryPointQueryResult q;
    cudaGetDriverEntryPoint("cuTensorMapEncodeTiled", &f, cudaEnableDefault, &q);
    enc = (EncodeFn)f;
    cudaFuncSetAttribute(fused_kernel, cudaFuncAttributeMaxDynamicSharedMemorySize, SMEM_BYTES);
  }
  void *xn, *H;
  cudaGetSymbolAddress(&xn, g_xn);
  cudaGetSymbolAddress(&H, g_H);
  Params P;
  P.x = (const __nv_bfloat16*)d_in[0];
  P.zero = 0; P.pad = 0;
  make_map(enc, &P.xn, xn, 2, DM, SEQ, 1, DM * 2, 0, 64, 128, 1);
  make_map(enc, &P.xin, d_in[0], 2, DM, SEQ, 1, DM * 2, 0, 64, 128, 1);
  make_map(enc, &P.H, H, 2, HW, SEQ, 1, HW * 2, 0, 64, 128, 1);
  make_map(enc, &P.out, d_out, 2, DM, SEQ, 1, DM * 2, 0, 64, 128, 1);
  make_map(enc, &P.wqkv, d_in[1], 3, DM, DM, 3, 3 * DM * 2, DM * 2, 64, 32, 3);
  make_map(enc, &P.wg1, d_in[4], 3, 64, DM, 72, FF * 2, 128, 64, 32, 1);
  make_map(enc, &P.wu1, d_in[5], 3, 64, DM, 72, FF * 2, 128, 64, 32, 1);
  make_map(enc, &P.wg2, d_in[4], 3, 64, DM, 72, FF * 2, 128, 64, 32, 2);
  make_map(enc, &P.wu2, d_in[5], 3, 64, DM, 72, FF * 2, 128, 64, 32, 2);
  make_map(enc, &P.wd, d_in[6], 3, 64, FF, 9, DM * 2, 128, 64, 32, 3);
  make_map(enc, &P.wo, d_in[2], 3, 64, DM, 9, DM * 2, 128, 64, 32, 3);
  build_schedule(P.sch);
  fused_kernel<<<NCTA, 512, SMEM_BYTES>>>(P);
}
```

```cpp
#include <cuda_runtime.h>
#include <cuda_bf16.h>
#include <cuda.h>
#include <stdint.h>

__device__ __forceinline__ void wgmma_ss_n192(float (&d)[96], uint32_t alo, uint32_t blo, int sd) {
  asm volatile("{\n.reg .pred p;\n.reg .b64 da, db;\nsetp.ne.b32 p, %98, 0;\nmov.b64 da, {%96, 0x40000040};\nmov.b64 db, {%97, 0x40000040};\n"
    "wgmma.mma_async.sync.aligned.m64n192k16.f32.bf16.bf16 {%0, %1, %2, %3, %4, %5, %6, %7, %8, %9, %10, %11, %12, %13, %14, %15, %16, %17, %18, %19, %20, %21, %22, %23, %24, %25, %26, %27, %28, %29, %30, %31, %32, %33, %34, %35, %36, %37, %38, %39, %40, %41, %42, %43, %44, %45, %46, %47, %48, %49, %50, %51, %52, %53, %54, %55, %56, %57, %58, %59, %60, %61, %62, %63, %64, %65, %66, %67, %68, %69, %70, %71, %72, %73, %74, %75, %76, %77, %78, %79, %80, %81, %82, %83, %84, %85, %86, %87, %88, %89, %90, %91, %92, %93, %94, %95}, da, db, p, 1, 1, 0, 1;\n}\n"
    : "+f"(d[0]), "+f"(d[1]), "+f"(d[2]), "+f"(d[3]), "+f"(d[4]), "+f"(d[5]), "+f"(d[6]), "+f"(d[7]), "+f"(d[8]), "+f"(d[9]), "+f"(d[10]), "+f"(d[11]), "+f"(d[12]), "+f"(d[13]), "+f"(d[14]), "+f"(d[15]), "+f"(d[16]), "+f"(d[17]), "+f"(d[18]), "+f"(d[19]), "+f"(d[20]), "+f"(d[21]), "+f"(d[22]), "+f"(d[23]), "+f"(d[24]), "+f"(d[25]), "+f"(d[26]), "+f"(d[27]), "+f"(d[28]), "+f"(d[29]), "+f"(d[30]), "+f"(d[31]), "+f"(d[32]), "+f"(d[33]), "+f"(d[34]), "+f"(d[35]), "+f"(d[36]), "+f"(d[37]), "+f"(d[38]), "+f"(d[39]), "+f"(d[40]), "+f"(d[41]), "+f"(d[42]), "+f"(d[43]), "+f"(d[44]), "+f"(d[45]), "+f"(d[46]), "+f"(d[47]), "+f"(d[48]), "+f"(d[49]), "+f"(d[50]), "+f"(d[51]), "+f"(d[52]), "+f"(d[53]), "+f"(d[54]), "+f"(d[55]), "+f"(d[56]), "+f"(d[57]), "+f"(d[58]), "+f"(d[59]), "+f"(d[60]), "+f"(d[61]), "+f"(d[62]), "+f"(d[63]), "+f"(d[64]), "+f"(d[65]), "+f"(d[66]), "+f"(d[67]), "+f"(d[68]), "+f"(d[69]), "+f"(d[70]), "+f"(d[71]), "+f"(d[72]), "+f"(d[73]), "+f"(d[74]), "+f"(d[75]), "+f"(d[76]), "+f"(d[77]), "+f"(d[78]), "+f"(d[79]), "+f"(d[80]), "+f"(d[81]), "+f"(d[82]), "+f"(d[83]), "+f"(d[84]), "+f"(d[85]), "+f"(d[86]), "+f"(d[87]), "+f"(d[88]), "+f"(d[89]), "+f"(d[90]), "+f"(d[91]), "+f"(d[92]), "+f"(d[93]), "+f"(d[94]), "+f"(d[95])
    : "r"(alo), "r"(blo), "r"(sd));
}
template <uint32_t BHI, int SD> __device__ __forceinline__ void wgmma_rs_n64(float (&d)[32], uint32_t a0, uint32_t a1, uint32_t a2, uint32_t a3, uint32_t blo) {
  asm volatile("{\n.reg .b64 db;\nmov.b64 db, {%36, %37};\n"
    "wgmma.mma_async.sync.aligned.m64n64k16.f32.bf16.bf16 {%0, %1, %2, %3, %4, %5, %6, %7, %8, %9, %10, %11, %12, %13, %14, %15, %16, %17, %18, %19, %20, %21, %22, %23, %24, %25, %26, %27, %28, %29, %30, %31}, {%32,%33,%34,%35}, db, %38, 1, 1, 0;\n}\n"
    : "+f"(d[0]), "+f"(d[1]), "+f"(d[2]), "+f"(d[3]), "+f"(d[4]), "+f"(d[5]), "+f"(d[6]), "+f"(d[7]), "+f"(d[8]), "+f"(d[9]), "+f"(d[10]), "+f"(d[11]), "+f"(d[12]), "+f"(d[13]), "+f"(d[14]), "+f"(d[15]), "+f"(d[16]), "+f"(d[17]), "+f"(d[18]), "+f"(d[19]), "+f"(d[20]), "+f"(d[21]), "+f"(d[22]), "+f"(d[23]), "+f"(d[24]), "+f"(d[25]), "+f"(d[26]), "+f"(d[27]), "+f"(d[28]), "+f"(d[29]), "+f"(d[30]), "+f"(d[31])
    : "r"(a0), "r"(a1), "r"(a2), "r"(a3), "r"(blo), "n"(BHI), "n"(SD));
}
template <uint32_t BHI, int SD> __device__ __forceinline__ void wgmma_rs_n24(float (&d)[12], uint32_t a0, uint32_t a1, uint32_t a2, uint32_t a3, uint32_t blo) {
  asm volatile("{\n.reg .b64 db;\nmov.b64 db, {%16, %17};\n"
    "wgmma.mma_async.sync.aligned.m64n24k16.f32.bf16.bf16 {%0, %1, %2, %3, %4, %5, %6, %7, %8, %9, %10, %11}, {%12,%13,%14,%15}, db, %18, 1, 1, 1;\n}\n"
    : "+f"(d[0]), "+f"(d[1]), "+f"(d[2]), "+f"(d[3]), "+f"(d[4]), "+f"(d[5]), "+f"(d[6]), "+f"(d[7]), "+f"(d[8]), "+f"(d[9]), "+f"(d[10]), "+f"(d[11])
    : "r"(a0), "r"(a1), "r"(a2), "r"(a3), "r"(blo), "n"(BHI), "n"(SD));
}

#define GP(...) __VA_ARGS__
#define HINT "20000"
#define PSLEEP 20
#define LSLEEP 50
namespace {

constexpr int SEQ = 2048, DM = 576, FF = 4608, HW = FF + DM;
constexpr int NCTA = 132, NATT = 128;
#define P_C1 26
#define P_C2 26
#define P_C3 28
#define P_F 22
constexpr int NL = 8, C1 = P_C1, C2 = P_C2, C3 = P_C3, CF = P_F;
constexpr int GST = 4, GSTB = 40960;
constexpr int KST = 5, KSTB = 6144;
constexpr int QB = 128 * 36;
constexpr int OFF_STG = GST * GSTB;
constexpr int OFF_KV = OFF_STG + 32768;
constexpr int OFF_Q = OFF_KV + KST * KSTB;
constexpr int OFF_BAR = OFF_Q + QB;
constexpr int SMEM_BYTES = OFF_BAR + 512;
constexpr int BH = 16384, BH2 = 12288;
constexpr float MBIAS = 72.f;

constexpr int FL_LN = 0;
constexpr int FL_QKV = 512;
constexpr int FL_H = 1024;
constexpr int FL_P = FL_H + 16 * 96;
constexpr int FL_DONE = FL_P + 48 * 3;
constexpr int FL_TOTAL = FL_DONE + 32;

struct Sched { uint8_t nseg, kind, m[4], n[4], k0[4], k1[4], kc[4], pad[2]; };
struct Params {
  CUtensorMap xn, H, H64, out, wqkv, wg1, wu1, wg2, wu2, wd, wo, xin;
  const __nv_bfloat16* x;
  uint32_t zero, pad;
  Sched sch[NCTA];
};

__device__ __align__(1024) __nv_bfloat16 g_xn[SEQ * DM];
__device__ __align__(1024) __nv_bfloat16 g_H[SEQ * HW];
__device__ __align__(1024) uint8_t g_q[32 * SEQ * 36];
__device__ __align__(1024) uint8_t g_kv[32 * 32 * KSTB];
__device__ __align__(1024) uint4 g_part[48 * 4 * 1536];
__device__ int g_flags[FL_TOTAL];
#define STAMP(i)
#define TIC(v)
#define TOC(acc, v)
#define PUT(i, val)

__device__ __forceinline__ void wg_fence() { asm volatile("wgmma.fence.sync.aligned;" ::: "memory"); }
__device__ __forceinline__ void wg_commit() { asm volatile("wgmma.commit_group.sync.aligned;" ::: "memory"); }
template <int N> __device__ __forceinline__ void wg_wait() { asm volatile("wgmma.wait_group.sync.aligned %0;" ::"n"(N) : "memory"); }
template <int N> __device__ __forceinline__ void pin(float (&d)[N]) {
#pragma unroll
  for (int i = 0; i < N; i++) asm volatile("" : "+f"(d[i])::"memory");
}
template <int N> __device__ __forceinline__ void pin(uint32_t (&d)[N]) {
#pragma unroll
  for (int i = 0; i < N; i++) asm volatile("" : "+r"(d[i])::"memory");
}
__device__ __forceinline__ uint32_t desc_lo(uint32_t addr, uint32_t lbo) { return ((addr & 0x3FFFF) >> 4) | ((lbo >> 4) << 16); }
__device__ __forceinline__ float ex2(float x) { float r; asm("ex2.approx.ftz.f32 %0, %1;" : "=f"(r) : "f"(x)); return r; }
__device__ __forceinline__ float tanhf_fast(float x) { float r; asm("tanh.approx.f32 %0, %1;" : "=f"(r) : "f"(x)); return r; }
__device__ __forceinline__ uint32_t pack2(float lo, float hi) { uint32_t r; asm("cvt.rn.bf16x2.f32 %0, %1, %2;" : "=r"(r) : "f"(hi), "f"(lo)); return r; }
__device__ __forceinline__ float bf_lo(uint32_t v) { float r; asm("shl.b32 %0, %1, 16;" : "=f"(r) : "r"(v)); return r; }
__device__ __forceinline__ float bf_hi(uint32_t v) { float r; asm("and.b32 %0, %1, 0xffff0000;" : "=f"(r) : "r"(v)); return r; }
__device__ __forceinline__ float bf_rn(float v) { return __bfloat162float(__float2bfloat16_rn(v)); }
__device__ __forceinline__ float fdiv(float a, float b) { float r; asm("div.full.f32 %0, %1, %2;" : "=f"(r) : "f"(a), "f"(b)); return r; }
__device__ __forceinline__ float fsqrt(float a) { float r; asm("sqrt.approx.f32 %0, %1;" : "=f"(r) : "f"(a)); return r; }
__device__ __forceinline__ int lane_id() { int l; asm volatile("mov.u32 %0, %%laneid;" : "=r"(l)); return l; }
__device__ __forceinline__ uint32_t clk32() { uint32_t c; asm volatile("mov.u32 %0, %%clock;" : "=r"(c)); return c; }

__device__ __forceinline__ void mbar_init(uint32_t a, uint32_t c) { asm volatile("mbarrier.init.shared::cta.b64 [%0], %1;" ::"r"(a), "r"(c) : "memory"); }
__device__ __forceinline__ void mbar_arrive(uint32_t a) { asm volatile("mbarrier.arrive.shared::cta.b64 _, [%0];" ::"r"(a) : "memory"); }
__device__ __forceinline__ bool mbar_test(uint32_t a, uint32_t ph) {
  uint32_t ok;
  asm volatile("{\n.reg .pred p;\nmbarrier.test_wait.parity.shared::cta.b64 p, [%1], %2;\nselp.u32 %0, 1, 0, p;\n}\n" : "=r"(ok) : "r"(a), "r"(ph) : "memory");
  return ok;
}
__device__ __forceinline__ void mbar_wait(uint32_t a, uint32_t ph) {
  asm volatile("{\n.reg .pred p;\n.reg .u32 n;\nmbarrier.try_wait.parity.shared::cta.b64 p, [%0], %1;\n@p bra D_%=;\nmov.u32 n, 0;\n"
               "W_%=:\nmbarrier.try_wait.parity.shared::cta.b64 p, [%0], %1, " HINT ";\n@p bra D_%=;\n"
               "add.u32 n, n, 1;\nsetp.lt.u32 p, n, 200000;\n@p bra W_%=;\ntrap;\nD_%=:\n}\n" ::"r"(a), "r"(ph) : "memory");
}
#define ELECT "{\n.reg .pred e;\nelect.sync _|e, 0xffffffff;\n@e "
__device__ __forceinline__ uint64_t policy_stream() {
  uint64_t p; asm("createpolicy.fractional.L2::evict_first.b64 %0, 1.0;" : "=l"(p)); return p;
}
__device__ __forceinline__ void expect1(uint32_t a, uint32_t b) { asm volatile(ELECT "mbarrier.arrive.expect_tx.shared::cta.b64 _, [%0], %1;\n}\n" ::"r"(a), "r"(b) : "memory"); }
__device__ __forceinline__ void arrive1(uint32_t a) { asm volatile(ELECT "mbarrier.arrive.shared::cta.b64 _, [%0];\n}\n" ::"r"(a) : "memory"); }
__device__ __forceinline__ void tma2d(uint32_t dst, const CUtensorMap* m, int c0, int c1, uint32_t bar) {
  asm volatile(ELECT "cp.async.bulk.tensor.2d.shared::cluster.global.mbarrier::complete_tx::bytes [%0], [%1, {%3, %4}], [%2];\n}\n"
               ::"r"(dst), "l"(m), "r"(bar), "r"(c0), "r"(c1) : "memory");
}
__device__ __forceinline__ void tma3d_mc(uint32_t dst, const CUtensorMap* m, int c0, int c1, int c2, uint32_t bar) {
  asm volatile(ELECT "cp.async.bulk.tensor.3d.shared::cluster.global.mbarrier::complete_tx::bytes.multicast::cluster [%0], [%1, {%3, %4, %5}], [%2], %6;\n}\n"
               ::"r"(dst), "l"(m), "r"(bar), "r"(c0), "r"(c1), "r"(c2), "h"((uint16_t)3) : "memory");
}
__device__ __forceinline__ void tma3d_mc_stream(uint32_t dst, const CUtensorMap* m, int c0, int c1, int c2, uint32_t bar, uint64_t pol) {
  asm volatile(ELECT "cp.async.bulk.tensor.3d.shared::cluster.global.mbarrier::complete_tx::bytes.multicast::cluster.L2::cache_hint [%0], [%1, {%3, %4, %5}], [%2], %6, %7;\n}\n"
               ::"r"(dst), "l"(m), "r"(bar), "r"(c0), "r"(c1), "r"(c2), "h"((uint16_t)3), "l"(pol) : "memory");
}
__device__ __forceinline__ void bulk_load(uint32_t dst, const void* src, uint32_t bytes, uint32_t bar, uint64_t pol) {
  asm volatile(ELECT "cp.async.bulk.shared::cluster.global.mbarrier::complete_tx::bytes.L2::cache_hint [%0], [%1], %2, [%3], %4;\n}\n"
               ::"r"(dst), "l"(src), "r"(bytes), "r"(bar), "l"(pol) : "memory");
}
__device__ __forceinline__ void bulk_load_mc(uint32_t dst, const void* src, uint32_t bytes, uint32_t bar, uint64_t pol) {
  asm volatile(ELECT "cp.async.bulk.shared::cluster.global.mbarrier::complete_tx::bytes.multicast::cluster.L2::cache_hint [%0], [%1], %2, [%3], %4, %5;\n}\n"
               ::"r"(dst), "l"(src), "r"(bytes), "r"(bar), "h"((uint16_t)3), "l"(pol) : "memory");
}
__device__ __forceinline__ uint32_t map_peer(uint32_t a, uint32_t rank) { uint32_t r; asm("mapa.shared::cluster.u32 %0, %1, %2;" : "=r"(r) : "r"(a), "r"(rank)); return r; }
__device__ __forceinline__ void arrive_cluster(uint32_t a) { asm volatile("mbarrier.arrive.relaxed.cluster.shared::cluster.b64 _, [%0];" ::"r"(a) : "memory"); }
__device__ __forceinline__ void arrive_cluster1(uint32_t a) { asm volatile(ELECT "mbarrier.arrive.relaxed.cluster.shared::cluster.b64 _, [%0];\n}\n" ::"r"(a) : "memory"); }
__device__ __forceinline__ void release_stage(uint32_t a, int lane) { if (lane < 2) arrive_cluster(map_peer(a, lane)); }
__device__ __forceinline__ void cluster_sync() { asm volatile("barrier.cluster.arrive.relaxed.aligned;\nbarrier.cluster.wait.aligned;" ::: "memory"); }
__device__ __forceinline__ int uni(int v) { return __shfl_sync(0xffffffffu, v, 0); }
__device__ __forceinline__ void tma2d_store(const CUtensorMap* m, int c0, int c1, uint32_t src) {
  asm volatile("cp.async.bulk.tensor.2d.global.shared::cta.bulk_group [%0, {%2, %3}], [%1];" ::"l"(m), "r"(src), "r"(c0), "r"(c1) : "memory");
}
__device__ __forceinline__ void pf3d(const CUtensorMap* m, int c0, int c1, int c2) {
  asm volatile("cp.async.bulk.prefetch.tensor.3d.L2.global [%0, {%1, %2, %3}];" ::"l"(m), "r"(c0), "r"(c1), "r"(c2) : "memory");
}
__device__ __forceinline__ void bulk_commit() { asm volatile("cp.async.bulk.commit_group;" ::: "memory"); }
__device__ __forceinline__ void bulk_wait0() { asm volatile("cp.async.bulk.wait_group 0;" ::: "memory"); }
__device__ __forceinline__ void fence_async_glob() { asm volatile("fence.proxy.async.global;" ::: "memory"); }
__device__ __forceinline__ void fence_cta() { asm volatile("fence.acq_rel.cta;" ::: "memory"); }
__device__ __forceinline__ void fence_release() { asm volatile("fence.release.gpu;" ::: "memory"); }
__device__ __forceinline__ void red_relaxed(int* p, int v = 1) { asm volatile("red.relaxed.gpu.global.add.s32 [%0], %1;" ::"l"(p), "r"(v) : "memory"); }
__device__ __forceinline__ void bar_arrive(int id, int n) { asm volatile("bar.arrive %0, %1;" ::"r"(id), "r"(n) : "memory"); }
__device__ __forceinline__ void bar_sync(int id, int n) { asm volatile("bar.sync %0, %1;" ::"r"(id), "r"(n) : "memory"); }
__device__ __forceinline__ void fence_async_smem() { asm volatile("fence.proxy.async.shared::cta;" ::: "memory"); }
__device__ __forceinline__ void red_release(int* p) { asm volatile("red.release.gpu.global.add.s32 [%0], 1;" ::"l"(p) : "memory"); }
__device__ __forceinline__ int ld_relaxed(const int* p) { int v; asm volatile("ld.relaxed.gpu.global.s32 %0, [%1];" : "=r"(v) : "l"(p) : "memory"); return v; }
__device__ __forceinline__ void fence_acquire() { asm volatile("fence.acquire.gpu;" ::: "memory"); }
__device__ __forceinline__ void stsm4(uint32_t a, uint32_t r0, uint32_t r1, uint32_t r2, uint32_t r3) {
  asm volatile("stmatrix.sync.aligned.m8n8.x4.shared.b16 [%0], {%1,%2,%3,%4};" ::"r"(a), "r"(r0), "r"(r1), "r"(r2), "r"(r3) : "memory");
}
__device__ __forceinline__ void ldsm4(uint32_t a, uint32_t& r0, uint32_t& r1, uint32_t& r2, uint32_t& r3) {
  asm volatile("ldmatrix.sync.aligned.m8n8.x4.shared.b16 {%0,%1,%2,%3}, [%4];" : "=r"(r0), "=r"(r1), "=r"(r2), "=r"(r3) : "r"(a) : "memory");
}
__device__ __forceinline__ uint32_t lds32(uint32_t a) { uint32_t v; asm volatile("ld.shared.u32 %0, [%1];" : "=r"(v) : "r"(a) : "memory"); return v; }
__device__ __forceinline__ uint4 lds128(uint32_t a) {
  uint4 v; asm volatile("ld.shared.v4.u32 {%0,%1,%2,%3}, [%4];" : "=r"(v.x), "=r"(v.y), "=r"(v.z), "=r"(v.w) : "r"(a) : "memory"); return v;
}
__device__ __forceinline__ void poll_ge(const int* p, int target) {
  const uint32_t t0 = clk32();
  while (!__all_sync(0xffffffffu, ld_relaxed(p) >= target)) { __nanosleep(PSLEEP); if (clk32() - t0 > 0x60000000u) __trap(); }
  fence_acquire();
}

__device__ __forceinline__ uint32_t xn_off(int kb) { return kb == 0 ? OFF_KV : ((kb + 1) & 3) * GSTB + (kb > 4 ? 8192 : 0); }
__device__ __forceinline__ void layernorm_rows(uint4 (&v)[9], uint32_t sb, int r, int grow, bool to_global, int lane) {
  float f[72];
  float s = 0.f;
#pragma unroll
  for (int i = 0; i < 9; i++) {
    f[8 * i] = bf_lo(v[i].x); f[8 * i + 1] = bf_hi(v[i].x); f[8 * i + 2] = bf_lo(v[i].y); f[8 * i + 3] = bf_hi(v[i].y);
    f[8 * i + 4] = bf_lo(v[i].z); f[8 * i + 5] = bf_hi(v[i].z); f[8 * i + 6] = bf_lo(v[i].w); f[8 * i + 7] = bf_hi(v[i].w);
    s += ((f[8 * i] + f[8 * i + 1]) + (f[8 * i + 2] + f[8 * i + 3])) + ((f[8 * i + 4] + f[8 * i + 5]) + (f[8 * i + 6] + f[8 * i + 7]));
  }
#pragma unroll
  for (int o = 4; o; o >>= 1) s += __shfl_xor_sync(0xffffffffu, s, o);
  const float mean = s * (1.f / DM);
  float q0 = 0.f, q1 = 0.f;
#pragma unroll
  for (int i = 0; i < 72; i += 2) { const float a = f[i] - mean, b = f[i + 1] - mean; q0 = fmaf(a, a, q0); q1 = fmaf(b, b, q1); }
  float q = q0 + q1;
#pragma unroll
  for (int o = 4; o; o >>= 1) q += __shfl_xor_sync(0xffffffffu, q, o);
  const float mb = bf_rn(mean);
  const float inv = fdiv(1.f, bf_rn(fsqrt(bf_rn(bf_rn(q * (1.f / DM)) + 1e-5f))));
  auto nrm = [&](int i) { const uint32_t d = pack2(f[i] - mb, f[i + 1] - mb); return pack2(bf_lo(d) * inv, bf_hi(d) * inv); };
  auto halve = [](uint32_t v) { return pack2(bf_lo(v) * 0.5f, bf_hi(v) * 0.5f); };
  uint4* g = reinterpret_cast<uint4*>(g_xn + (size_t)grow * DM) + (lane & 7);
#pragma unroll
  for (int i = 0; i < 9; i++) {
    const uint4 o = make_uint4(nrm(8 * i), nrm(8 * i + 2), nrm(8 * i + 4), nrm(8 * i + 6));
    asm volatile("st.shared.v4.u32 [%0], {%1,%2,%3,%4};" ::"r"(sb + xn_off(i) + r * 128 + (((lane ^ r) & 7) << 4)), "r"(o.x), "r"(o.y), "r"(o.z), "r"(o.w) : "memory");
    if (to_global) g[8 * i] = make_uint4(halve(o.x), halve(o.y), halve(o.z), halve(o.w));
  }
  fence_async_smem();
}

__device__ __forceinline__ void attn_row_slow(int head, int row, int lane) {
  const uint8_t* qp = g_q + (size_t)head * (SEQ * 36) + row * 36;
  float q[18], o[18];
#pragma unroll
  for (int d = 0; d < 18; d += 2) {
    uint32_t v = *reinterpret_cast<const volatile uint32_t*>(qp + d * 2);
    q[d] = bf_lo(v); q[d + 1] = bf_hi(v); o[d] = 0.f; o[d + 1] = 0.f;
  }
  float m = -INFINITY, l = 0.f;
#pragma unroll 1
  for (int key = lane; key < SEQ; key += 32) {
    const uint8_t* kp = g_kv + (size_t)head * (32 * KSTB) + (key >> 6) * KSTB + ((key >> 3) & 7) * 384 + (key & 7) * 16;
    float s = 0.f;
#pragma unroll
    for (int d = 0; d < 18; d += 2) {
      uint32_t v = *reinterpret_cast<const volatile uint32_t*>(kp + (d >> 3) * 128 + (d & 7) * 2);
      s = fmaf(q[d], bf_lo(v), s); s = fmaf(q[d + 1], bf_hi(v), s);
    }
    const float mn = fmaxf(m, s), c = ex2(m - mn), p = ex2(s - mn);
    m = mn; l = l * c + p;
#pragma unroll
    for (int d = 0; d < 18; d += 2) {
      uint32_t v = *reinterpret_cast<const volatile uint32_t*>(kp + 3072 + (d >> 3) * 128 + (d & 7) * 2);
      o[d] = fmaf(p, bf_lo(v), o[d] * c); o[d + 1] = fmaf(p, bf_hi(v), o[d + 1] * c);
    }
  }
  float M = m;
#pragma unroll
  for (int t = 16; t; t >>= 1) M = fmaxf(M, __shfl_xor_sync(0xffffffffu, M, t));
  const float c = ex2(m - M);
  l *= c;
#pragma unroll
  for (int t = 16; t; t >>= 1) l += __shfl_xor_sync(0xffffffffu, l, t);
  uint32_t* dst = reinterpret_cast<uint32_t*>(g_H + (size_t)row * HW + FF + head * 18);
#pragma unroll
  for (int d = 0; d < 18; d += 2) {
    float a = o[d] * c, b = o[d + 1] * c;
#pragma unroll
    for (int t = 16; t; t >>= 1) { a += __shfl_xor_sync(0xffffffffu, a, t); b += __shfl_xor_sync(0xffffffffu, b, t); }
    if (lane == 0) dst[d >> 1] = pack2(fdiv(a, l), fdiv(b, l));
  }
}

constexpr uint32_t AB = (BH >> 4) + (255u << 16);
template <int MODE>
__device__ __forceinline__ void gemm_run(float (&a0)[96], float (&a1)[96], int nk, int keep, int& st, uint32_t& ph, uint32_t dA,
                                         uint32_t bar_full, int lane, uint32_t& gw) {
  constexpr bool BOTH = MODE == 0;
  uint32_t da = dA + st * (GSTB >> 4);
  uint32_t rel = 0;
  int kb = 0;
  pin(a0); if (BOTH) pin(a1);
#pragma unroll 1
  do {
    wg_fence();
    const uint32_t aa = MODE != 1 ? da : dA + (xn_off(kb) >> 4);
    wgmma_ss_n192(a0, aa, da + AB, kb | keep);
    wg_commit();
    wg_wait<1>();
    if (rel) release_stage(rel, lane);
    if (BOTH) {
      wgmma_ss_n192(a1, da + 512, da + AB, kb | keep);
      wg_commit();
      wg_wait<1>();
    }
    rel = bar_full + 32 + 8 * st;
    if (++st == GST) { st = 0; ph ^= 1; }
    bool ready = false;
#pragma unroll
    for (int k = 1; k < 4; k++) {
      if (k == 3) ready = mbar_test(bar_full + 8 * st, ph);
      wgmma_ss_n192(a0, aa + 2 * k, da + AB + (k >> 1) * (BH2 >> 4) + (k & 1) * 128, 1);
      wg_commit();
      if (BOTH) {
        wg_wait<1>();
        wgmma_ss_n192(a1, da + 512 + 2 * k, da + AB + (k >> 1) * (BH2 >> 4) + (k & 1) * 128, 1);
        wg_commit();
      }
      if (k < 3) wg_wait<1>();
    }
    da = dA + st * (GSTB >> 4);
    if (++kb < nk && !ready) { TIC(t0); mbar_wait(bar_full + 8 * st, ph); TOC(gw, t0); }
    wg_wait<1>();
  } while (kb < nk);
  wg_wait<0>();
  pin(a0); if (BOTH) pin(a1);
  release_stage(rel, lane);
}

template <bool ODD>
__device__ __forceinline__ void glu_epilogue(const float (&E)[96], uint32_t s0) {
#pragma unroll
  for (int g = 0; g < 8; g += 2) {
    uint32_t h[4], w[4];
    if (ODD) ldsm4((s0 + 16384) ^ (g << 4), w[0], w[1], w[2], w[3]);
#pragma unroll
    for (int i = 0; i < 4; i++) {
      const int e = 4 * g + 2 * i;
      if (ODD) {
        h[i] = pack2(fmaf(tanhf_fast(E[64 + e]), E[32 + e], E[32 + e]), fmaf(tanhf_fast(E[65 + e]), E[33 + e], E[33 + e]));
        w[i] = pack2(bf_lo(w[i]) * E[e], bf_hi(w[i]) * E[e + 1]);
      } else {
        h[i] = pack2(fmaf(tanhf_fast(E[e]), E[64 + e], E[64 + e]), fmaf(tanhf_fast(E[e + 1]), E[65 + e], E[65 + e]));
        w[i] = pack2(tanhf_fast(E[32 + e]) + 1.f, tanhf_fast(E[33 + e]) + 1.f);
      }
    }
    stsm4(s0 ^ (g << 4), h[0], h[1], h[2], h[3]);
    stsm4((s0 + 16384) ^ (g << 4), w[0], w[1], w[2], w[3]);
  }
}

__device__ __forceinline__ void qkv_scatter(uint32_t tile, int rb, int a, int w, int hoff, int hstep, int lane) {
  const int r8 = lane >> 2, j = lane & 3;
  const int h0 = ((a * 64 * 3641) >> 16) + hoff;
  uint8_t* const qb = g_q + rb * 288 + lane * 4;
  uint8_t* const kb = g_kv + (rb >> 3) * KSTB + (rb & 7) * 384 + r8 * 16 + j * 4;
  const uint32_t row = tile + (w * 16 + r8) * 400 + 128;
#pragma unroll 1
  for (int h = h0; h * 18 < a * 64 + 64; h += hstep) {
    uint32_t v[3][4], q[5];
    bool data[3], qd[5];
    const int col0 = h * 18 - a * 64;
#pragma unroll
    for (int i = 0; i < 5; i++) {
      const int wd = lane + 32 * i, r = (wd * 57) >> 9, col = col0 + 2 * (wd - 9 * r);
      qd[i] = wd < 144 && (unsigned)col < 64u;
      q[i] = lds32(tile + (qd[i] ? (w * 16 + r) * 400 + col * 2 : 0));
    }
#pragma unroll
    for (int c = 0; c < 3; c++) {
      const int col = col0 + c * 8 + 2 * j;
      data[c] = (unsigned)col < 64u && (c < 2 || j == 0);
      const uint32_t src = row + (data[c] ? col : 0) * 2;
#pragma unroll
      for (int e = 0; e < 4; e++) v[c][e] = lds32(src + (e >> 1) * 128 + (e & 1) * 3200);
    }
    const bool pad = j > 0 && (unsigned)(col0 + 16) < 64u;
    if (j > 0) { v[2][0] = v[2][1] = j == 1 ? 0x3f803f80u : 0u; v[2][2] = v[2][3] = j == 1 ? 0x00003f80u : 0u; }
    uint8_t* const kp = kb + h * (32 * KSTB);
#pragma unroll
    for (int c = 0; c < 3; c++)
      if (data[c] || (c == 2 && pad)) {
        *reinterpret_cast<uint32_t*>(kp + c * 128) = v[c][0]; *reinterpret_cast<uint32_t*>(kp + c * 128 + 384) = v[c][1];
        *reinterpret_cast<uint32_t*>(kp + c * 128 + 3072) = v[c][2]; *reinterpret_cast<uint32_t*>(kp + c * 128 + 3456) = v[c][3];
      }
    uint8_t* const qp = qb + h * (SEQ * 36);
#pragma unroll
    for (int i = 0; i < 5; i++) if (qd[i]) *reinterpret_cast<uint32_t*>(qp + i * 128) = q[i];
  }
}

__global__ void __cluster_dims__(2, 1, 1) __launch_bounds__(512, 1) fused_kernel(const __grid_constant__ Params P) {
  extern __shared__ __align__(1024) uint8_t smem_raw[];
  const uint32_t sb = (uint32_t)__cvta_generic_to_shared(smem_raw);
  if (sb & 1023u) __trap();
  const uint32_t bar_gfull = sb + OFF_BAR, bar_gempty = bar_gfull + 32;
  const uint32_t bar_kfull = bar_gfull + 256, bar_kempty = bar_kfull + 80;
  const uint32_t bar_gdone = bar_gfull + 160, bar_gfree = bar_gfull + 168, bar_odone = bar_gfull + 176, bar_qdone = bar_gfull + 184, bar_xfree = bar_gfull + 200;
  const uint32_t bar_kpeer = bar_kfull + 160;
  const int tid = threadIdx.x;
  const int warp = __shfl_sync(0xffffffffu, tid >> 5, 0);
  const int wg = warp >> 2;
  const int cta = blockIdx.x;
  const bool att = cta < NATT;
  const int cm = cta & 15, cj = cta >> 4;
  const Sched& sch = P.sch[cta];
  const int nq = att ? 2 : 4, ngu = att ? 6 : 0;
  const int qa = att ? cta >> 5 : 8, qrow = att ? (cta & 31) * 64 : (cta - NATT) * 512;

  if (tid == 384) {
    for (int i = 0; i < GST; i++) { mbar_init(bar_gfull + 8 * i, 1); mbar_init(bar_gempty + 8 * i, 8); }
        for (int i = 0; i <= KST; i++) { mbar_init(bar_kfull + 8 * i, 1); mbar_init(bar_kempty + 8 * i, 8); }
    mbar_init(bar_gdone, 4); mbar_init(bar_gfree, 1); mbar_init(bar_odone, 8); mbar_init(bar_qdone, 8); mbar_init(bar_xfree, 4);
    for (int i = 0; i < KST; i++) mbar_init(bar_kpeer + 8 * i, 1);
    asm volatile("fence.mbarrier_init.release.cluster;" ::: "memory");
    fence_async_smem();
    STAMP(0);
  }
  uint4 xv[9];
  const int lrow = ((warp * 4 + (qa - 1) * 16) & 63) + ((tid & 31) >> 3);
  if (att) {
    const uint4* xr = reinterpret_cast<const uint4*>(P.x + (size_t)(qrow + lrow) * DM) + (tid & 7);
#pragma unroll
    for (int i = 0; i < 9; i++) xv[i] = __ldg(xr + 8 * i);
  }
  if (tid >= 480 && tid < 492) asm volatile("prefetch.tensormap [%0];" ::"l"(&P.xn + (tid - 480)) : "memory");
  __syncwarp();
  cluster_sync();
  if (warp == 0) STAMP(30);
  const int rank = cta & 1;
  if (warp == 12)
    for (int i = 0; i < GST; i++) {
      expect1(bar_gfull + 8 * i, att ? GSTB - BH : GSTB);
      tma3d_mc(sb + i * GSTB + BH + rank * BH2, &P.wqkv, qa * 64, i * 64 + rank * 32, 0, bar_gfull + 8 * i);
    }
  if (tid == 416 && cm < 10) pf3d(&P.wqkv, qa * 64, GST * 64 + cm * 32, 0);
  if (tid == 448 && att && (cta & 31) < 18) pf3d(&P.wqkv, (qa + 4) * 64, (cta & 31) * 32, 0);
  __syncwarp();
  if (att) {
    layernorm_rows(xv, sb, lrow, qrow + lrow, wg == 1, tid & 31);
    if (warp == 0) STAMP(38);
    if (wg == 0) bar_sync(4, 512); else bar_arrive(4, 512);
    if (warp == 0) STAMP(39);
    if (wg == 1) {
      fence_async_glob();
      __syncwarp();
      if ((tid & 31) == 0) { fence_release(); red_relaxed(g_flags + FL_LN + (qrow >> 7) * 32, 4); }
    }
  }

  if (wg == 3) {
    asm volatile("setmaxnreg.dec.sync.aligned.u32 24;");
    const int pw = warp & 3, lane = lane_id();
    const bool el = lane == 0;
    if (pw == 0) {
      int st = 0; uint32_t ph = 1;
      const uint64_t pol = policy_stream();
      auto acquire = [&](uint32_t bytes) -> uint32_t {
        mbar_wait(bar_gempty + 8 * st, ph);
        expect1(bar_gfull + 8 * st, bytes);
        return sb + st * GSTB;
      };
      auto advance = [&]() { if (++st == GST) { st = 0; ph ^= 1; } };
      if (att) {
        ph ^= 1;
#pragma unroll 1
        for (int i = GST; i < 18; i++) {
          const uint32_t s = acquire(GSTB - BH);
          tma3d_mc(s + BH + rank * BH2, &P.wqkv, (i < 9 ? qa : qa + 4) * 64, (i < 9 ? i : i - 9) * 64 + rank * 32, 0, bar_gfull + 8 * st);
          advance();
        }
      } else {
#pragma unroll 1
        for (int t = 0; t < 4; t++) {
          const int row = uni(qrow + t * 128);
          int kb = 0;
          poll_ge(g_flags + FL_LN + (row >> 7) * 32, 128);
          fence_async_glob();
          if (t == 0) {
            STAMP(1);
            for (int i = 0; i < GST; i++) tma2d(sb + i * GSTB, &P.xn, i * 64, row, bar_gfull + 8 * i);
            kb = GST; ph ^= 1;
          }
          st = uni(st); ph = uni(ph); kb = uni(kb);
#pragma unroll 1
          for (; kb < 9; kb++) {
            const uint32_t s = acquire(GSTB);
            tma2d(s, &P.xn, kb * 64, row, bar_gfull + 8 * st);
            tma3d_mc(s + BH + rank * BH2, &P.wqkv, 8 * 64, kb * 64 + rank * 32, 0, bar_gfull + 8 * st);
            advance();
          }
        }
      }
      if (att) { poll_ge(g_flags + FL_LN + cm * 32, 128); fence_async_glob(); }
#pragma unroll 1
      for (int t = 0; t < ngu; t++) {
        const int a0 = uni((cj + 8 * (t >> 1)) * 3), hf = uni(t & 1);
        const CUtensorMap* m2 = hf ? &P.wu2 : &P.wg2; const CUtensorMap* m1 = hf ? &P.wg1 : &P.wu1;
        const int x2 = a0 + hf, x1 = a0 + 2 * hf;
        if (hf && t < 5 && lane < 7) {
          const int b = cm + 16 * lane;
          if (b < 108) pf3d(b < 54 ? &P.wg1 : &P.wu1, 0, ((b % 54) / 3) * 32, a0 + 24 + b % 3);
        }
        if (t == 2 && lane < 4) {
          const int b = cta + 128 * lane;
          if (b < 432) pf3d(&P.wd, 0, (b / 3) * 32, (b % 3) * 3);
          else if (b < 486) pf3d(&P.wo, 0, ((b - 432) / 3) * 32, ((b - 432) % 3) * 3);
        }
        st = uni(st); ph = uni(ph);
#pragma unroll 1
        for (int kb = 0; kb < 9; kb++) {
          const uint32_t s = acquire(GSTB), b = bar_gfull + 8 * st;
          tma2d(s, &P.xn, kb * 64, cm * 128, b);
          tma3d_mc_stream(s + BH + rank * BH2, m2, 0, kb * 64 + rank * 32, x2, b, pol);
          tma3d_mc_stream(s + BH + rank * BH2 + 8192, m1, 0, kb * 64 + rank * 32, x1, b, pol);
          advance();
        }
      }
      auto wait_h = [&](int m, int kb, int k1) -> int {
        const uint32_t t0 = clk32();
        const int i = kb + lane;
        uint32_t b;
        while (true) {
          bool ok = false;
          if (i < k1) ok = ld_relaxed(g_flags + FL_H + m * 96 + i) >= (i < 72 ? 1 : 32 + 8 * (i & 1));
          b = __ballot_sync(0xffffffffu, ok);
          if (b & 1) break;
          __nanosleep(kb >= 78 ? LSLEEP : 200);
          if (clk32() - t0 > 0x60000000u) __trap();
        }
        fence_acquire();
        fence_async_glob();
        return uni(kb + (b == 0xffffffffu ? 32 : __ffs(~b) - 1));
      };
      auto down_range = [&](int m, int n, int k0, int k1) {
#pragma unroll 1
        for (int kb = k0; kb < k1;) {
          const int ready = wait_h(m, kb, k1);
          st = uni(st); ph = uni(ph); kb = uni(kb); m = uni(m); n = uni(n);
          const CUtensorMap* mw = kb < 72 ? &P.wd : &P.wo;
          const int y0 = rank * 32 - (kb < 72 ? 0 : 72 * 64);
#pragma unroll 1
          for (; kb < ready; kb++) {
            const uint32_t s = acquire(GSTB), b = bar_gfull + 8 * st;
            tma2d(s, &P.H, kb * 64, m * 128, b);
            tma3d_mc(s + BH + rank * BH2, mw, 0, kb * 64 + y0, n * 3, b);
            advance();
          }
        }
      };
      const int kind = sch.kind;
#pragma unroll 1
      for (int i = 0; i < sch.nseg; i++) {
        const int va = sch.k0[i], vb = sch.k1[i], ne = sch.kc[i] - NL;
#pragma unroll 1
        for (int h = 0; h < (kind == 1 ? 4 : 2); h++) {
          int k0, k1;
          if (kind == 1) { k0 = h == 0 ? 72 : h == 1 ? ne : h == 2 ? 48 + NL : 76; k1 = h == 0 ? 76 : h == 1 ? 48 : h == 2 ? 72 : 78; }
          else { k0 = h ? (va > ne ? va : ne) + 48 - ne : va; k1 = h ? vb + 48 - ne : (vb < ne ? vb : ne); }
          down_range(sch.m[i], sch.n[i], k0, k1);
        }
      }
      if (kind) {
        const int m = sch.m[0], n = sch.n[0], tile = m * 3 + n, row = m * 128 + (kind - 1) * 64;
        {
          const uint32_t s = acquire(24576);
          for (int c = 0; c < 3; c++) tma2d(s + c * 8192, &P.xin, n * 192 + c * 64, row, bar_gfull + 8 * st);
          advance();
        }
#pragma unroll 1
        for (int p = 0; p < 2; p++) {
          poll_ge(g_flags + FL_P + tile * 3 + p * (3 - kind), 1);
          fence_async_glob();
          const uint32_t s = acquire(24576);
          bulk_load(s, g_part + (tile * 4 + p * 2 + kind - 1) * 1536, 24576, bar_gfull + 8 * st, pol);
          advance();
        }
#pragma unroll 1
        for (int kb = 78; kb < 81;) {
          const int ready = wait_h(m, kb, 81);
          st = uni(st); ph = uni(ph); kb = uni(kb);
#pragma unroll 1
          for (; kb < ready; kb++) {
            const uint32_t s = acquire(GSTB - 8192), b = bar_gfull + 8 * st;
            tma2d(s, &P.H64, kb * 64, row, b);
            tma3d_mc(s + BH + rank * BH2, &P.wo, 0, (kb - 72) * 64 + rank * 32, n * 3, b);
            advance();
          }
        }
      }
    } else if (pw == 1) {
      if (att) {
        const uint64_t pol = policy_stream();
        const uint32_t peer = map_peer(bar_kpeer, rank ^ 1);
        uint32_t st = 0, ph = 0;
        int m = 0;
#pragma unroll 1
        for (int r = 0; r < 5; r++) {
          if (r < 4) {
            const int head = r * 8 + cj, atom = (head * 18 + (lane & 1) * 17) >> 6;
            poll_ge(g_flags + FL_QKV + atom * 32, atom < 8 ? 256 : 128);
            fence_async_glob();
            mbar_wait(bar_kempty + 8 * KST, (r & 1) ^ 1);
            expect1(bar_kfull + 8 * KST, QB);
            bulk_load(sb + OFF_Q, g_q + head * (SEQ * 36) + cm * QB, QB, bar_kfull + 8 * KST, pol);
            if (r == 0) STAMP(2);
          }
          if (r == 0) mbar_wait(bar_xfree, 0);
          const int mend = uni(r < 3 ? r * 32 + 27 : (r == 3 ? 0 : 129));
          st = uni(st); ph = uni(ph); m = uni(m);
#pragma unroll 1
          for (; m < mend; m++) {
            const int n = m - rank;
            mbar_wait(bar_kempty + 8 * st, ph ^ 1);
            arrive_cluster1(peer + 8 * st);
            expect1(bar_kfull + 8 * st, (unsigned)(m - 1) < 127u ? KSTB : 3072);
            mbar_wait(bar_kpeer + 8 * st, ph);
            if ((unsigned)n < 128u)
              bulk_load_mc(sb + OFF_KV + st * KSTB + rank * 3072, g_kv + (uint32_t)((((n >> 5) * 8 + cj) * 32 + (n & 31)) * KSTB + rank * 3072), 3072,
                           bar_kfull + 8 * st, pol);
            if (++st == KST) { st = 0; ph ^= 1; }
          }
        }
      }
    } else if (pw == 2) {
      if (att) {
        mbar_wait(bar_qdone, 0);
        mbar_wait(bar_qdone, 1);
        if (el) { fence_async_glob(); fence_release(); red_relaxed(g_flags + FL_QKV + (qa + 4) * 32, 8); }
        __syncwarp();
      }
      const int nt = ngu + sch.nseg;
#pragma unroll 1
      for (int u = 0; u < nt; u++) {
        mbar_wait(bar_gdone, u & 1);
        if (el) {
          if (u < ngu) {
            const int a0 = (cj + 8 * (u >> 1)) * 3;
            if (u & 1) { tma2d_store(&P.H, (a0 + 1) * 64, cm * 128, sb + OFF_STG + 16384); tma2d_store(&P.H, (a0 + 2) * 64, cm * 128, sb + OFF_STG); }
            else tma2d_store(&P.H, a0 * 64, cm * 128, sb + OFF_STG);
            bulk_commit(); bulk_wait0();
            fence_release();
            if (u & 1) { red_relaxed(g_flags + FL_H + cm * 96 + a0 + 1); red_relaxed(g_flags + FL_H + cm * 96 + a0 + 2); }
            else red_relaxed(g_flags + FL_H + cm * 96 + a0);
          } else {
            fence_async_glob();
            red_release(g_flags + FL_P + (sch.m[u - ngu] * 3 + sch.n[u - ngu]) * 3 + sch.kind);
          }
          mbar_arrive(bar_gfree);
          if (u == ngu - 1) STAMP(35);
          if (u == nt - 1) STAMP(36);
        }
        __syncwarp();
      }
    } else {
      if (att) {
        if (lane < 7) {
          const int b = cm + 16 * lane;
          if (b < 108) pf3d(b < 54 ? &P.wg1 : &P.wu1, 0, ((b % 54) / 3) * 32, cj * 3 + b % 3);
        }
        for (int r = 0; r < 3; r++) {
          mbar_wait(bar_odone, r & 1);
          if (el) {
            const int head = r * 8 + cj, a0 = (head * 18) >> 6, a1 = (head * 18 + 17) >> 6;
            fence_async_glob();
            fence_release();
            red_relaxed(g_flags + FL_H + cm * 96 + 72 + a0, 8);
            if (a1 != a0) red_relaxed(g_flags + FL_H + cm * 96 + 72 + a1, 8);
          }
          __syncwarp();
        }
      }
    }
    if (pw == 0 || (pw == 1 && att)) {
      int old = 0;
      if (el) { __threadfence(); old = atomicAdd(g_flags + FL_DONE, 1); __threadfence(); }
      old = __shfl_sync(0xffffffffu, old, 0);
      if (old == NCTA + NATT - 1) for (int i = lane; i < FL_TOTAL; i += 32) g_flags[i] = 0;
    }
  } else if (wg >= 1) {
    const int lane = lane_id();
#pragma unroll 1
    for (int t = 0; t < nq; t++) {
      bar_sync(1, 384);
      if (att) qkv_scatter(sb + OFF_STG, (qrow >> 3) + (warp & 3) * 2, qa + 4 * t, warp & 3, wg - 1, 2, lane);
      else qkv_scatter(sb + OFF_STG, (qrow >> 3) + t * 16 + (warp - 4) * 2, 8, warp - 4, 0, 1, lane);
      fence_cta();
      __syncwarp();
      if (lane == 0) {
        mbar_arrive(bar_qdone);
        if (!att || !t) { fence_async_glob(); red_release(g_flags + FL_QKV + qa * 32); }
      }
      if (warp == 4) STAMP(t ? 34 : 32);
    }
    if (att) {
      const int wa = warp - 4;
      const int r8 = lane >> 2, j = lane & 3;
      const uint32_t kvd = __shfl_sync(0xffffffffu, desc_lo(sb + OFF_KV, 0), 0);
      const uint32_t kb0 = __shfl_sync(0xffffffffu, bar_kfull, 0);
      constexpr uint32_t DK = 8u << 16, DK2 = 16, DV = (24u << 16) + 192;
      const uint32_t qa = sb + OFF_Q + (wa * 16 + r8) * 36 + j * 4;
      uint32_t q[8], p[16];
      float s[32], s2[32], o[12];
      auto load_q = [&](int r) {
        mbar_wait(kb0 + 8 * KST, r & 1);
        q[0] = lds32(qa); q[1] = lds32(qa + 288); q[2] = lds32(qa + 16); q[3] = lds32(qa + 304);
        q[4] = j == 0 ? lds32(qa + 32) : 0u; q[5] = j == 0 ? lds32(qa + 320) : 0u; q[6] = 0u; q[7] = 0u;
      };
      load_q(0);
      mbar_wait(kb0, 0);
      pin(q);
      wg_fence();
      wgmma_rs_n64<24, 0>(s, q[0], q[1], q[2], q[3], kvd + DK);
      wgmma_rs_n64<24, 1>(s, q[4], q[5], q[6], q[7], kvd + DK2);
      wg_commit();
      mbar_wait(kb0 + 8, 0);
      wg_wait<0>();
      pin(s);
#pragma unroll
      for (int i = 0; i < 32; i++) s2[i] = 0.f;
#pragma unroll
      for (int i = 0; i < 16; i++) p[i] = 0u;
      uint32_t cur = uni(1), prev = uni(0), nph = uni(0);
      auto step = [&](float (&a)[32], float (&b)[32], int special) {
        const uint32_t d = kvd + cur * (KSTB >> 4);
        const uint32_t nxt = cur + 1 == KST ? 0 : cur + 1;
        nph ^= nxt == 0;
        pin(b); pin(q);
        wg_fence();
        wgmma_rs_n64<24, 0>(b, q[0], q[1], q[2], q[3], d + DK);
        wgmma_rs_n64<24, 1>(b, q[4], q[5], q[6], q[7], d + DK2);
        wg_commit();
#pragma unroll
        for (int i = 0; i < 32; i++) a[i] = ex2(a[i]);
        pin(a);
        wg_wait<1>();
        pin(p); pin(o);
        arrive1(kb0 + 80 + 8 * prev);
        const bool ready = mbar_test(kb0 + 8 * nxt, nph);
#pragma unroll
        for (int i = 0; i < 16; i++) p[i] = pack2(a[2 * i], a[2 * i + 1]);
        pin(p);
        wg_fence();
#pragma unroll
        for (int k = 0; k < 4; k++)
          wgmma_rs_n24<8, 1>(o, p[4 * k], p[4 * k + 1], p[4 * k + 2], p[4 * k + 3], d + DV + k * 48);
        wg_commit();
        if (!ready && special < 4) mbar_wait(kb0 + 8 * nxt, nph);
        wg_wait<1>();
        pin(b);
        prev = cur; cur = nxt;
      };
      auto new_rows = [&]() {
        if (lane == 0) mbar_arrive(kb0 + 80 + 8 * KST);
        {
          float m0 = fmaxf(s[0], s[1]), m1 = fmaxf(s[2], s[3]);
#pragma unroll
          for (int i = 4; i < 32; i += 4) { m0 = fmaxf(m0, fmaxf(s[i], s[i + 1])); m1 = fmaxf(m1, fmaxf(s[i + 2], s[i + 3])); }
          m0 = fmaxf(m0, __shfl_xor_sync(0xffffffffu, m0, 1)); m1 = fmaxf(m1, __shfl_xor_sync(0xffffffffu, m1, 1));
          m0 = fmaxf(m0, __shfl_xor_sync(0xffffffffu, m0, 2)); m1 = fmaxf(m1, __shfl_xor_sync(0xffffffffu, m1, 2));
          m0 = -(m0 + MBIAS); m1 = -(m1 + MBIAS);
          const float h0 = bf_rn(m0), h1 = bf_rn(m1), l0 = bf_rn(m0 - h0), l1 = bf_rn(m1 - h1);
          if (j == 1) { q[4] = pack2(h0, l0); q[5] = pack2(h1, l1); }
          m0 = h0 + l0; m1 = h1 + l1;
#pragma unroll
          for (int i = 0; i < 32; i += 4) { s[i] += m0; s[i + 1] += m0; s[i + 2] += m1; s[i + 3] += m1; }
        }
      };
      new_rows();
#pragma unroll 1
      for (int r = 0; r < 4; r++) {
        const int head = r * 8 + cj;
        TIC(tb);
#pragma unroll
        for (int i = 0; i < 12; i++) o[i] = 0.f;
        TOC(aw, tb);
        const int nq1 = uni(r < 3 ? 15 : -1), nl = uni(r == 3 ? 15 : -1);
        nph = uni(nph);
#pragma unroll 1
        for (int n = uni(0); n < 16; n++) {
          step(s, s2, 0);
          if (n == nq1) load_q(r + 1);
          step(s2, s, n == nl ? 4 : 0);
        }
        if (r < 3) new_rows();
        wg_wait<0>();
        pin(o); pin(s);
        TIC(te);
        const float l0 = __shfl_sync(0xffffffffu, o[8], (lane & ~3) | 1), l1 = __shfl_sync(0xffffffffu, o[10], (lane & ~3) | 1);
        float lo0 = fminf(fminf(fabsf(o[0]), fabsf(o[1])), fminf(fabsf(o[4]), fabsf(o[5])));
        float lo1 = fminf(fminf(fabsf(o[2]), fabsf(o[3])), fminf(fabsf(o[6]), fabsf(o[7])));
        float z0 = (o[0] + o[1] + o[4] + o[5]) * 0.f, z1 = (o[2] + o[3] + o[6] + o[7]) * 0.f;
        if (j == 0) {
          lo0 = fminf(lo0, fminf(fabsf(o[8]), fabsf(o[9]))); lo1 = fminf(lo1, fminf(fabsf(o[10]), fabsf(o[11])));
          z0 += (o[8] + o[9]) * 0.f; z1 += (o[10] + o[11]) * 0.f;
        }
        const bool ok0 = l0 >= 0x1p-90f && l0 <= 0x1p125f && lo0 >= l0 * 0x1p-33f && z0 == 0.f;
        const bool ok1 = l1 >= 0x1p-90f && l1 <= 0x1p125f && lo1 >= l1 * 0x1p-33f && z1 == 0.f;
        const int row = cm * 128 + wa * 16 + r8;
        {
          const float i0 = fdiv(1.f, l0), i1 = fdiv(1.f, l1);
          uint32_t* d0 = reinterpret_cast<uint32_t*>(g_H + (size_t)row * HW + FF + head * 18) + j;
          uint32_t* d1 = d0 + 8 * (HW / 2);
          d0[0] = pack2(o[0] * i0, o[1] * i0); d0[4] = pack2(o[4] * i0, o[5] * i0);
          d1[0] = pack2(o[2] * i1, o[3] * i1); d1[4] = pack2(o[6] * i1, o[7] * i1);
          if (j == 0) { d0[8] = pack2(o[8] * i0, o[9] * i0); d1[8] = pack2(o[10] * i1, o[11] * i1); }
        }
        const uint32_t bad0 = __ballot_sync(0xffffffffu, !ok0), bad1 = __ballot_sync(0xffffffffu, !ok1);
        if (bad0 | bad1) {
          __syncwarp();
#pragma unroll 1
          for (int rr = 0; rr < 16; rr++)
            if (((rr < 8 ? bad0 : bad1) >> ((rr & 7) * 4)) & 15u) attn_row_slow(head, cm * 128 + wa * 16 + rr, lane);
        }
        if (r < 3) {
          fence_cta();
          __syncwarp();
          if (lane == 0) mbar_arrive(bar_odone);
        } else {
          fence_async_glob();
          __syncwarp();
          if (lane == 0) {
            const int a0 = (head * 18) >> 6, a1 = (head * 18 + 17) >> 6;
            fence_release();
            red_relaxed(g_flags + FL_H + cm * 96 + 72 + a0);
            if (a1 != a0) red_relaxed(g_flags + FL_H + cm * 96 + 72 + a1);
          }
        }
        TOC(aw, te);
        if (wa == 0) { STAMP(4 + r); PUT(56, aw); PUT(57, am); PUT(59, nr); PUT(60 + r, ak); }
        if (wa == 4) { PUT(24 + r, clk32() - c0); PUT(28, nr); PUT(58, clk32() - c0); }
      }
    }
  } else {
    asm volatile("setmaxnreg.inc.sync.aligned.u32 232;");
    const int lane = lane_id();
    float acc0[96], acc1[96];
#pragma unroll
    for (int i = 0; i < 96; i++) asm volatile("" : "=f"(acc0[i]), "=f"(acc1[i]));
    int st = 0; uint32_t ph = 0;
    const uint32_t dA = __shfl_sync(0xffffffffu, desc_lo(sb, 16), 0);
    const uint32_t soff = (warp * 16 + (lane & 15)) * 128 + (((lane >> 4) ^ (lane & 7)) << 4);
    const int ntask = nq + sch.nseg, kind = sch.kind;
    uint32_t gw = 0;
#pragma unroll 1
    for (int t = 0; t < ntask; t++) {
      if (t == nq && ngu) {
#pragma unroll 1
        for (int u = 0; u < 6; u++) {
          mbar_wait(bar_gfull + 8 * st, ph);
          gemm_run<0>(acc0, acc1, 9, 0, st, ph, dA, bar_gfull, lane, gw);
          GP(if (warp == 0) STAMP(10 + 2 * u);)
          if (u) mbar_wait(bar_gfree, (u - 1) & 1); else mbar_wait(bar_qdone, 1);
          const uint32_t s4 = sb + OFF_STG + soff;
          if (u & 1) { glu_epilogue<true>(acc0, s4); glu_epilogue<true>(acc1, s4 + 8192); }
          else { glu_epilogue<false>(acc0, s4); glu_epilogue<false>(acc1, s4 + 8192); }
          fence_async_smem();
          __syncwarp();
          if (lane == 0) mbar_arrive(bar_gdone);
          GP(if (warp == 0) STAMP(11 + 2 * u);)
        }
      }
      const int sg = t - nq, u = sg < 0 ? sg : sg + ngu;
      int nk = 9;
      if (sg >= 0) nk = kind == 1 ? 78 - sch.kc[0] : sch.k1[sg] - sch.k0[sg];
      { TIC(t0); mbar_wait(bar_gfull + 8 * st, ph); TOC(gw, t0); }
      if (att && t < 2) gemm_run<1>(acc0, acc1, nk, 0, st, ph, dA, bar_gfull, lane, gw);
      else gemm_run<0>(acc0, acc1, nk, 0, st, ph, dA, bar_gfull, lane, gw);
      if (att && t == 1 && lane == 0) mbar_arrive(bar_xfree);
      GP(if (warp == 0) { STAMP(8 + 2 * (u < 0 ? 0 : u + 1)); PUT(44 + (u < 0 ? 0 : u + 1), gw); })
      if (u < 0) { if (t > 0) mbar_wait(bar_qdone, (t - 1) & 1); }
      else if (u > 0) mbar_wait(bar_gfree, (u - 1) & 1);
      if (u < 0) {
        const float qs = 0.23570226039551584f * 1.4426950408889634f;
        const float xs = att ? 1.f : 2.f;
        auto st_qkv = [&](float (&acc)[96], uint32_t pa) {
#pragma unroll
          for (int g = 0; g < 24; g += 2) {
            const float f = g < 8 ? qs * xs : xs;
            stsm4(pa + g * 16, pack2(acc[4 * g] * f, acc[4 * g + 1] * f), pack2(acc[4 * g + 2] * f, acc[4 * g + 3] * f),
                  pack2(acc[4 * g + 4] * f, acc[4 * g + 5] * f), pack2(acc[4 * g + 6] * f, acc[4 * g + 7] * f));
          }
        };
        const uint32_t pa = sb + OFF_STG + (warp * 16 + (lane & 15)) * 400 + (lane >> 4) * 16;
        st_qkv(acc0, pa);
        if (!att) st_qkv(acc1, pa + 64 * 400);
        bar_arrive(1, 384);
      } else {
        {
          uint4* pp = g_part + ((sch.m[sg] * 3 + sch.n[sg]) * 4 + (kind ? 2 : 0)) * 1536 + warp * 32 + lane;
          auto put = [&](const float (&acc)[96], uint4* q) {
#pragma unroll
            for (int i = 0; i < 12; i++)
              q[i * 128] = make_uint4(pack2(acc[8 * i], acc[8 * i + 1]), pack2(acc[8 * i + 2], acc[8 * i + 3]),
                                      pack2(acc[8 * i + 4], acc[8 * i + 5]), pack2(acc[8 * i + 6], acc[8 * i + 7]));
          };
          if (kind != 1) put(acc0, pp);
          if (kind != 2) put(acc1, pp + 1536);
          fence_cta();
        }
        __syncwarp();
        if (lane == 0) mbar_arrive(bar_gdone);
      }
      GP(if (warp == 0) { STAMP(9 + 2 * (u < 0 ? 0 : u + 1)); if (t == 0) STAMP(33); })
    }
    if (kind) {
      if (kind == 2) {
#pragma unroll
        for (int i = 0; i < 96; i++) acc0[i] = acc1[i];
      }
      {
        mbar_wait(bar_gfull + 8 * st, ph);
        uint32_t dep = 0;
#pragma unroll
        for (int g = 0; g < 24; g += 2) {
          uint32_t w[4];
          ldsm4((sb + st * GSTB + (g >> 3) * 8192 + soff) ^ ((g & 7) << 4), w[0], w[1], w[2], w[3]);
          dep |= w[3];
#pragma unroll
          for (int i = 0; i < 4; i++) { acc0[4 * g + 2 * i] += bf_lo(w[i]); acc0[4 * g + 2 * i + 1] += bf_hi(w[i]); }
        }
        release_stage(bar_gempty + 8 * st + (dep & P.zero), lane);
        if (++st == GST) { st = 0; ph ^= 1; }
      }
#pragma unroll 1
      for (int pp = 0; pp < 2; pp++) {
        mbar_wait(bar_gfull + 8 * st, ph);
        const uint32_t a = sb + st * GSTB + (warp * 32 + lane) * 16;
        uint32_t dep = 0;
#pragma unroll
        for (int i = 0; i < 12; i++) {
          const uint4 v = lds128(a + i * 2048);
          dep |= v.w;
          acc0[8 * i] += bf_lo(v.x); acc0[8 * i + 1] += bf_hi(v.x); acc0[8 * i + 2] += bf_lo(v.y); acc0[8 * i + 3] += bf_hi(v.y);
          acc0[8 * i + 4] += bf_lo(v.z); acc0[8 * i + 5] += bf_hi(v.z); acc0[8 * i + 6] += bf_lo(v.w); acc0[8 * i + 7] += bf_hi(v.w);
        }
        release_stage(bar_gempty + 8 * st + (dep & P.zero), lane);
        if (++st == GST) { st = 0; ph ^= 1; }
      }
      GP(if (warp == 0) STAMP(40);)
      mbar_wait(bar_gfull + 8 * st, ph);
      gemm_run<2>(acc0, acc1, 3, 1, st, ph, dA, bar_gfull, lane, gw);
      GP(if (warp == 0) STAMP(41);)
#pragma unroll
      for (int g = 0; g < 24; g += 2)
        stsm4((sb + OFF_STG + (g >> 3) * 8192 + soff) ^ ((g & 7) << 4), pack2(acc0[4 * g], acc0[4 * g + 1]), pack2(acc0[4 * g + 2], acc0[4 * g + 3]),
              pack2(acc0[4 * g + 4], acc0[4 * g + 5]), pack2(acc0[4 * g + 6], acc0[4 * g + 7]));
      fence_async_smem();
      bar_sync(12, 128);
      if (warp == 0 && lane == 0) {
        for (int a = 0; a < 3; a++) tma2d_store(&P.out, sch.n[0] * 192 + a * 64, sch.m[0] * 128 + (kind - 1) * 64, sb + OFF_STG + a * 8192);
        bulk_commit(); bulk_wait0();
      }
      if (warp == 0) STAMP(42);
    }
  }
  __syncwarp();
  cluster_sync();
}

typedef CUresult (*EncodeFn)(CUtensorMap*, CUtensorMapDataType, cuuint32_t, void*, const cuuint64_t*, const cuuint64_t*, const cuuint32_t*,
                             const cuuint32_t*, CUtensorMapInterleave, CUtensorMapSwizzle, CUtensorMapL2promotion, CUtensorMapFloatOOBfill);

void make_map(EncodeFn enc, CUtensorMap* m, const void* ptr, int rank, uint64_t d0, uint64_t d1, uint64_t d2, uint64_t s1, uint64_t s2,
              uint32_t b0, uint32_t b1, uint32_t b2) {
  cuuint64_t gd[3] = {d0, d1, d2}, gs[2] = {s1, s2};
  cuuint32_t bd[3] = {b0, b1, b2}, es[3] = {1, 1, 1};
  enc(m, CU_TENSOR_MAP_DATA_TYPE_BFLOAT16, rank, const_cast<void*>(ptr), gd, gs, bd, es, CU_TENSOR_MAP_INTERLEAVE_NONE,
      CU_TENSOR_MAP_SWIZZLE_128B, CU_TENSOR_MAP_L2_PROMOTION_L2_256B, CU_TENSOR_MAP_FLOAT_OOB_FILL_NONE);
}

void build_schedule(Sched* s) {
  for (int i = 0; i < NCTA; i++) s[i] = Sched{};
  auto add = [&](int pair, int kind, int tp, int k0, int k1, int kc) {
    for (int r = 0; r < 2; r++) {
      Sched& c = s[2 * pair + r];
      c.kind = kind; c.m[c.nseg] = 2 * (tp / 3) + r; c.n[c.nseg] = tp % 3; c.k0[c.nseg] = k0; c.k1[c.nseg] = k1; c.kc[c.nseg] = kc; c.nseg++;
    }
  };
  for (int t = 0; t < 24; t++) {
    const int c = t < 8 ? CF : C1, kc = c + (t < 8 ? C3 : C2);
    add(t < 8 ? 64 + t / 4 : 40 + t, 0, t, 0, c, kc);
    add(t, 1, t, 0, 0, kc);
    add(24 + t, 2, t, c, kc, kc);
  }
}

}

extern "C" void kernel_launch(void* const* d_in, const int* in_sizes, int n_in, void* d_out, int out_size) {
  static EncodeFn enc = nullptr;
  if (!enc) {
    void* f = nullptr; cudaDriverEntryPointQueryResult q;
    cudaGetDriverEntryPoint("cuTensorMapEncodeTiled", &f, cudaEnableDefault, &q);
    enc = (EncodeFn)f;
    cudaFuncSetAttribute(fused_kernel, cudaFuncAttributeMaxDynamicSharedMemorySize, SMEM_BYTES);
  }
  void *xn, *H;
  cudaGetSymbolAddress(&xn, g_xn);
  cudaGetSymbolAddress(&H, g_H);
  Params P;
  P.x = (const __nv_bfloat16*)d_in[0];
  P.zero = 0; P.pad = 0;
  make_map(enc, &P.xn, xn, 2, DM, SEQ, 1, DM * 2, 0, 64, 128, 1);
  make_map(enc, &P.xin, d_in[0], 2, DM, SEQ, 1, DM * 2, 0, 64, 64, 1);
  make_map(enc, &P.H64, H, 2, HW, SEQ, 1, HW * 2, 0, 64, 64, 1);
  make_map(enc, &P.H, H, 2, HW, SEQ, 1, HW * 2, 0, 64, 128, 1);
  make_map(enc, &P.out, d_out, 2, DM, SEQ, 1, DM * 2, 0, 64, 64, 1);
  make_map(enc, &P.wqkv, d_in[1], 3, DM, DM, 3, 3 * DM * 2, DM * 2, 64, 32, 3);
  make_map(enc, &P.wg1, d_in[4], 3, 64, DM, 72, FF * 2, 128, 64, 32, 1);
  make_map(enc, &P.wu1, d_in[5], 3, 64, DM, 72, FF * 2, 128, 64, 32, 1);
  make_map(enc, &P.wg2, d_in[4], 3, 64, DM, 72, FF * 2, 128, 64, 32, 2);
  make_map(enc, &P.wu2, d_in[5], 3, 64, DM, 72, FF * 2, 128, 64, 32, 2);
  make_map(enc, &P.wd, d_in[6], 3, 64, FF, 9, DM * 2, 128, 64, 32, 3);
  make_map(enc, &P.wo, d_in[2], 3, 64, DM, 9, DM * 2, 128, 64, 32, 3);
  build_schedule(P.sch);
  fused_kernel<<<NCTA, 512, SMEM_BYTES>>>(P);
}
```

```cpp
#include <cuda_runtime.h>
#include <cuda_bf16.h>
#include <cuda.h>
#include <stdint.h>

__device__ __forceinline__ void wgmma_ss_n192(float (&d)[96], uint32_t alo, uint32_t blo, int sd) {
  asm volatile("{\n.reg .pred p;\n.reg .b64 da, db;\nsetp.ne.b32 p, %98, 0;\nmov.b64 da, {%96, 0x40000040};\nmov.b64 db, {%97, 0x40000040};\n"
    "wgmma.mma_async.sync.aligned.m64n192k16.f32.bf16.bf16 {%0, %1, %2, %3, %4, %5, %6, %7, %8, %9, %10, %11, %12, %13, %14, %15, %16, %17, %18, %19, %20, %21, %22, %23, %24, %25, %26, %27, %28, %29, %30, %31, %32, %33, %34, %35, %36, %37, %38, %39, %40, %41, %42, %43, %44, %45, %46, %47, %48, %49, %50, %51, %52, %53, %54, %55, %56, %57, %58, %59, %60, %61, %62, %63, %64, %65, %66, %67, %68, %69, %70, %71, %72, %73, %74, %75, %76, %77, %78, %79, %80, %81, %82, %83, %84, %85, %86, %87, %88, %89, %90, %91, %92, %93, %94, %95}, da, db, p, 1, 1, 0, 1;\n}\n"
    : "+f"(d[0]), "+f"(d[1]), "+f"(d[2]), "+f"(d[3]), "+f"(d[4]), "+f"(d[5]), "+f"(d[6]), "+f"(d[7]), "+f"(d[8]), "+f"(d[9]), "+f"(d[10]), "+f"(d[11]), "+f"(d[12]), "+f"(d[13]), "+f"(d[14]), "+f"(d[15]), "+f"(d[16]), "+f"(d[17]), "+f"(d[18]), "+f"(d[19]), "+f"(d[20]), "+f"(d[21]), "+f"(d[22]), "+f"(d[23]), "+f"(d[24]), "+f"(d[25]), "+f"(d[26]), "+f"(d[27]), "+f"(d[28]), "+f"(d[29]), "+f"(d[30]), "+f"(d[31]), "+f"(d[32]), "+f"(d[33]), "+f"(d[34]), "+f"(d[35]), "+f"(d[36]), "+f"(d[37]), "+f"(d[38]), "+f"(d[39]), "+f"(d[40]), "+f"(d[41]), "+f"(d[42]), "+f"(d[43]), "+f"(d[44]), "+f"(d[45]), "+f"(d[46]), "+f"(d[47]), "+f"(d[48]), "+f"(d[49]), "+f"(d[50]), "+f"(d[51]), "+f"(d[52]), "+f"(d[53]), "+f"(d[54]), "+f"(d[55]), "+f"(d[56]), "+f"(d[57]), "+f"(d[58]), "+f"(d[59]), "+f"(d[60]), "+f"(d[61]), "+f"(d[62]), "+f"(d[63]), "+f"(d[64]), "+f"(d[65]), "+f"(d[66]), "+f"(d[67]), "+f"(d[68]), "+f"(d[69]), "+f"(d[70]), "+f"(d[71]), "+f"(d[72]), "+f"(d[73]), "+f"(d[74]), "+f"(d[75]), "+f"(d[76]), "+f"(d[77]), "+f"(d[78]), "+f"(d[79]), "+f"(d[80]), "+f"(d[81]), "+f"(d[82]), "+f"(d[83]), "+f"(d[84]), "+f"(d[85]), "+f"(d[86]), "+f"(d[87]), "+f"(d[88]), "+f"(d[89]), "+f"(d[90]), "+f"(d[91]), "+f"(d[92]), "+f"(d[93]), "+f"(d[94]), "+f"(d[95])
    : "r"(alo), "r"(blo), "r"(sd));
}
template <uint32_t BHI, int SD> __device__ __forceinline__ void wgmma_rs_n64(float (&d)[32], uint32_t a0, uint32_t a1, uint32_t a2, uint32_t a3, uint32_t blo) {
  asm volatile("{\n.reg .b64 db;\nmov.b64 db, {%36, %37};\n"
    "wgmma.mma_async.sync.aligned.m64n64k16.f32.bf16.bf16 {%0, %1, %2, %3, %4, %5, %6, %7, %8, %9, %10, %11, %12, %13, %14, %15, %16, %17, %18, %19, %20, %21, %22, %23, %24, %25, %26, %27, %28, %29, %30, %31}, {%32,%33,%34,%35}, db, %38, 1, 1, 0;\n}\n"
    : "+f"(d[0]), "+f"(d[1]), "+f"(d[2]), "+f"(d[3]), "+f"(d[4]), "+f"(d[5]), "+f"(d[6]), "+f"(d[7]), "+f"(d[8]), "+f"(d[9]), "+f"(d[10]), "+f"(d[11]), "+f"(d[12]), "+f"(d[13]), "+f"(d[14]), "+f"(d[15]), "+f"(d[16]), "+f"(d[17]), "+f"(d[18]), "+f"(d[19]), "+f"(d[20]), "+f"(d[21]), "+f"(d[22]), "+f"(d[23]), "+f"(d[24]), "+f"(d[25]), "+f"(d[26]), "+f"(d[27]), "+f"(d[28]), "+f"(d[29]), "+f"(d[30]), "+f"(d[31])
    : "r"(a0), "r"(a1), "r"(a2), "r"(a3), "r"(blo), "n"(BHI), "n"(SD));
}
template <uint32_t BHI, int SD> __device__ __forceinline__ void wgmma_rs_n24(float (&d)[12], uint32_t a0, uint32_t a1, uint32_t a2, uint32_t a3, uint32_t blo) {
  asm volatile("{\n.reg .b64 db;\nmov.b64 db, {%16, %17};\n"
    "wgmma.mma_async.sync.aligned.m64n24k16.f32.bf16.bf16 {%0, %1, %2, %3, %4, %5, %6, %7, %8, %9, %10, %11}, {%12,%13,%14,%15}, db, %18, 1, 1, 1;\n}\n"
    : "+f"(d[0]), "+f"(d[1]), "+f"(d[2]), "+f"(d[3]), "+f"(d[4]), "+f"(d[5]), "+f"(d[6]), "+f"(d[7]), "+f"(d[8]), "+f"(d[9]), "+f"(d[10]), "+f"(d[11])
    : "r"(a0), "r"(a1), "r"(a2), "r"(a3), "r"(blo), "n"(BHI), "n"(SD));
}

namespace {

constexpr int SEQ = 2048, DM = 576, FF = 4608, HW = FF + DM;
constexpr int NCTA = 132, NATT = 128;
constexpr int NL = 8, C1 = 26, C2 = 26, C3 = 28, CF = 22;
constexpr int GST = 4, GSTB = 40960;
constexpr int KST = 6, KSTB = 5120;
constexpr int QB = 128 * 36;
constexpr int OFF_STG = GST * GSTB;
constexpr int OFF_KV = OFF_STG + 32768;
constexpr int OFF_Q = OFF_KV + KST * KSTB;
constexpr int OFF_BAR = OFF_Q + QB;
constexpr int SMEM_BYTES = OFF_BAR + 512;
constexpr int BH = 16384, BH2 = 12288;
constexpr float MBIAS = 72.f;

constexpr int FL_LN = 0;
constexpr int FL_QKV = 512;
constexpr int FL_H = 1024;
constexpr int FL_P = FL_H + 16 * 96;
constexpr int FL_DONE = FL_P + 48 * 3;
constexpr int FL_TOTAL = FL_DONE + 32;

struct Sched { uint8_t nseg, kind, m[4], n[4], k0[4], k1[4], kc[4], pad[2]; };
struct Params {
  CUtensorMap xn, H, H64, out, wqkv, wg1, wu1, wg2, wu2, wd, wo, xin;
  const __nv_bfloat16* x;
  uint32_t zero, pad;
  Sched sch[NCTA];
};

__device__ __align__(1024) __nv_bfloat16 g_xn[SEQ * DM];
__device__ __align__(1024) __nv_bfloat16 g_H[SEQ * HW];
__device__ __align__(1024) uint8_t g_q[32 * SEQ * 36];
__device__ __align__(1024) uint8_t g_kv[32 * 32 * KSTB];
__device__ __align__(1024) uint4 g_part[48 * 4 * 1536];
__device__ int g_flags[FL_TOTAL];

__device__ __forceinline__ void wg_fence() { asm volatile("wgmma.fence.sync.aligned;" ::: "memory"); }
__device__ __forceinline__ void wg_commit() { asm volatile("wgmma.commit_group.sync.aligned;" ::: "memory"); }
template <int N> __device__ __forceinline__ void wg_wait() { asm volatile("wgmma.wait_group.sync.aligned %0;" ::"n"(N) : "memory"); }
template <int N> __device__ __forceinline__ void pin(float (&d)[N]) {
#pragma unroll
  for (int i = 0; i < N; i++) asm volatile("" : "+f"(d[i])::"memory");
}
template <int N> __device__ __forceinline__ void pin(uint32_t (&d)[N]) {
#pragma unroll
  for (int i = 0; i < N; i++) asm volatile("" : "+r"(d[i])::"memory");
}
__device__ __forceinline__ uint32_t desc_lo(uint32_t addr, uint32_t lbo) { return ((addr & 0x3FFFF) >> 4) | ((lbo >> 4) << 16); }
__device__ __forceinline__ float ex2(float x) { float r; asm("ex2.approx.ftz.f32 %0, %1;" : "=f"(r) : "f"(x)); return r; }
__device__ __forceinline__ float tanhf_fast(float x) { float r; asm("tanh.approx.f32 %0, %1;" : "=f"(r) : "f"(x)); return r; }
__device__ __forceinline__ uint32_t pack2(float lo, float hi) { uint32_t r; asm("cvt.rn.bf16x2.f32 %0, %1, %2;" : "=r"(r) : "f"(hi), "f"(lo)); return r; }
__device__ __forceinline__ float bf_lo(uint32_t v) { float r; asm("shl.b32 %0, %1, 16;" : "=f"(r) : "r"(v)); return r; }
__device__ __forceinline__ float bf_hi(uint32_t v) { float r; asm("and.b32 %0, %1, 0xffff0000;" : "=f"(r) : "r"(v)); return r; }
__device__ __forceinline__ float bf_rn(float v) { return __bfloat162float(__float2bfloat16_rn(v)); }
__device__ __forceinline__ float fdiv(float a, float b) { float r; asm("div.full.f32 %0, %1, %2;" : "=f"(r) : "f"(a), "f"(b)); return r; }
__device__ __forceinline__ float fsqrt(float a) { float r; asm("sqrt.approx.f32 %0, %1;" : "=f"(r) : "f"(a)); return r; }
__device__ __forceinline__ int lane_id() { int l; asm volatile("mov.u32 %0, %%laneid;" : "=r"(l)); return l; }
__device__ __forceinline__ uint32_t clk32() { uint32_t c; asm volatile("mov.u32 %0, %%clock;" : "=r"(c)); return c; }

__device__ __forceinline__ void mbar_init(uint32_t a, uint32_t c) { asm volatile("mbarrier.init.shared::cta.b64 [%0], %1;" ::"r"(a), "r"(c) : "memory"); }
__device__ __forceinline__ void mbar_arrive(uint32_t a) { asm volatile("mbarrier.arrive.shared::cta.b64 _, [%0];" ::"r"(a) : "memory"); }
__device__ __forceinline__ bool mbar_test(uint32_t a, uint32_t ph) {
  uint32_t ok;
  asm volatile("{\n.reg .pred p;\nmbarrier.test_wait.parity.shared::cta.b64 p, [%1], %2;\nselp.u32 %0, 1, 0, p;\n}\n" : "=r"(ok) : "r"(a), "r"(ph) : "memory");
  return ok;
}
__device__ __forceinline__ void mbar_wait(uint32_t a, uint32_t ph) {
  asm volatile("{\n.reg .pred p;\n.reg .u32 n;\nmbarrier.try_wait.parity.shared::cta.b64 p, [%0], %1;\n@p bra D_%=;\nmov.u32 n, 0;\n"
               "W_%=:\nmbarrier.try_wait.parity.shared::cta.b64 p, [%0], %1, 20000;\n@p bra D_%=;\n"
               "add.u32 n, n, 1;\nsetp.lt.u32 p, n, 200000;\n@p bra W_%=;\ntrap;\nD_%=:\n}\n" ::"r"(a), "r"(ph) : "memory");
}
#define ELECT "{\n.reg .pred e;\nelect.sync _|e, 0xffffffff;\n@e "
__device__ __forceinline__ uint64_t policy_stream() {
  uint64_t p; asm("createpolicy.fractional.L2::evict_first.b64 %0, 1.0;" : "=l"(p)); return p;
}
__device__ __forceinline__ void expect1(uint32_t a, uint32_t b) { asm volatile(ELECT "mbarrier.arrive.expect_tx.shared::cta.b64 _, [%0], %1;\n}\n" ::"r"(a), "r"(b) : "memory"); }
__device__ __forceinline__ void arrive1(uint32_t a) { asm volatile(ELECT "mbarrier.arrive.shared::cta.b64 _, [%0];\n}\n" ::"r"(a) : "memory"); }
__device__ __forceinline__ void tma2d(uint32_t dst, const CUtensorMap* m, int c0, int c1, uint32_t bar) {
  asm volatile(ELECT "cp.async.bulk.tensor.2d.shared::cluster.global.mbarrier::complete_tx::bytes [%0], [%1, {%3, %4}], [%2];\n}\n"
               ::"r"(dst), "l"(m), "r"(bar), "r"(c0), "r"(c1) : "memory");
}
__device__ __forceinline__ void tma3d_mc(uint32_t dst, const CUtensorMap* m, int c0, int c1, int c2, uint32_t bar) {
  asm volatile(ELECT "cp.async.bulk.tensor.3d.shared::cluster.global.mbarrier::complete_tx::bytes.multicast::cluster [%0], [%1, {%3, %4, %5}], [%2], %6;\n}\n"
               ::"r"(dst), "l"(m), "r"(bar), "r"(c0), "r"(c1), "r"(c2), "h"((uint16_t)3) : "memory");
}
__device__ __forceinline__ void tma3d_mc_stream(uint32_t dst, const CUtensorMap* m, int c0, int c1, int c2, uint32_t bar, uint64_t pol) {
  asm volatile(ELECT "cp.async.bulk.tensor.3d.shared::cluster.global.mbarrier::complete_tx::bytes.multicast::cluster.L2::cache_hint [%0], [%1, {%3, %4, %5}], [%2], %6, %7;\n}\n"
               ::"r"(dst), "l"(m), "r"(bar), "r"(c0), "r"(c1), "r"(c2), "h"((uint16_t)3), "l"(pol) : "memory");
}
__device__ __forceinline__ void bulk_load(uint32_t dst, const void* src, uint32_t bytes, uint32_t bar, uint64_t pol) {
  asm volatile(ELECT "cp.async.bulk.shared::cluster.global.mbarrier::complete_tx::bytes.L2::cache_hint [%0], [%1], %2, [%3], %4;\n}\n"
               ::"r"(dst), "l"(src), "r"(bytes), "r"(bar), "l"(pol) : "memory");
}
__device__ __forceinline__ void bulk_load_mc(uint32_t dst, const void* src, uint32_t bytes, uint32_t bar, uint64_t pol) {
  asm volatile(ELECT "cp.async.bulk.shared::cluster.global.mbarrier::complete_tx::bytes.multicast::cluster.L2::cache_hint [%0], [%1], %2, [%3], %4, %5;\n}\n"
               ::"r"(dst), "l"(src), "r"(bytes), "r"(bar), "h"((uint16_t)3), "l"(pol) : "memory");
}
__device__ __forceinline__ uint32_t map_peer(uint32_t a, uint32_t rank) { uint32_t r; asm("mapa.shared::cluster.u32 %0, %1, %2;" : "=r"(r) : "r"(a), "r"(rank)); return r; }
__device__ __forceinline__ void arrive_cluster(uint32_t a) { asm volatile("mbarrier.arrive.relaxed.cluster.shared::cluster.b64 _, [%0];" ::"r"(a) : "memory"); }
__device__ __forceinline__ void arrive_cluster1(uint32_t a) { asm volatile(ELECT "mbarrier.arrive.relaxed.cluster.shared::cluster.b64 _, [%0];\n}\n" ::"r"(a) : "memory"); }
__device__ __forceinline__ void release_stage(uint32_t a, int lane) { if (lane < 2) arrive_cluster(map_peer(a, lane)); }
__device__ __forceinline__ void cluster_sync() { asm volatile("barrier.cluster.arrive.relaxed.aligned;\nbarrier.cluster.wait.aligned;" ::: "memory"); }
__device__ __forceinline__ int uni(int v) { return __shfl_sync(0xffffffffu, v, 0); }
__device__ __forceinline__ void tma2d_store(const CUtensorMap* m, int c0, int c1, uint32_t src) {
  asm volatile("cp.async.bulk.tensor.2d.global.shared::cta.bulk_group [%0, {%2, %3}], [%1];" ::"l"(m), "r"(src), "r"(c0), "r"(c1) : "memory");
}
__device__ __forceinline__ void pf3d(const CUtensorMap* m, int c0, int c1, int c2) {
  asm volatile("cp.async.bulk.prefetch.tensor.3d.L2.global [%0, {%1, %2, %3}];" ::"l"(m), "r"(c0), "r"(c1), "r"(c2) : "memory");
}
__device__ __forceinline__ void bulk_commit() { asm volatile("cp.async.bulk.commit_group;" ::: "memory"); }
__device__ __forceinline__ void bulk_wait0() { asm volatile("cp.async.bulk.wait_group 0;" ::: "memory"); }
__device__ __forceinline__ void fence_async_glob() { asm volatile("fence.proxy.async.global;" ::: "memory"); }
__device__ __forceinline__ void fence_cta() { asm volatile("fence.acq_rel.cta;" ::: "memory"); }
__device__ __forceinline__ void fence_release() { asm volatile("fence.release.gpu;" ::: "memory"); }
__device__ __forceinline__ void red_relaxed(int* p, int v = 1) { asm volatile("red.relaxed.gpu.global.add.s32 [%0], %1;" ::"l"(p), "r"(v) : "memory"); }
__device__ __forceinline__ void bar_arrive(int id, int n) { asm volatile("bar.arrive %0, %1;" ::"r"(id), "r"(n) : "memory"); }
__device__ __forceinline__ void bar_sync(int id, int n) { asm volatile("bar.sync %0, %1;" ::"r"(id), "r"(n) : "memory"); }
__device__ __forceinline__ void fence_async_smem() { asm volatile("fence.proxy.async.shared::cta;" ::: "memory"); }
__device__ __forceinline__ void red_release(int* p) { asm volatile("red.release.gpu.global.add.s32 [%0], 1;" ::"l"(p) : "memory"); }
__device__ __forceinline__ int ld_relaxed(const int* p) { int v; asm volatile("ld.relaxed.gpu.global.s32 %0, [%1];" : "=r"(v) : "l"(p) : "memory"); return v; }
__device__ __forceinline__ void fence_acquire() { asm volatile("fence.acquire.gpu;" ::: "memory"); }
__device__ __forceinline__ void stsm4(uint32_t a, uint32_t r0, uint32_t r1, uint32_t r2, uint32_t r3) {
  asm volatile("stmatrix.sync.aligned.m8n8.x4.shared.b16 [%0], {%1,%2,%3,%4};" ::"r"(a), "r"(r0), "r"(r1), "r"(r2), "r"(r3) : "memory");
}
__device__ __forceinline__ void ldsm4(uint32_t a, uint32_t& r0, uint32_t& r1, uint32_t& r2, uint32_t& r3) {
  asm volatile("ldmatrix.sync.aligned.m8n8.x4.shared.b16 {%0,%1,%2,%3}, [%4];" : "=r"(r0), "=r"(r1), "=r"(r2), "=r"(r3) : "r"(a) : "memory");
}
__device__ __forceinline__ uint32_t lds32(uint32_t a) { uint32_t v; asm volatile("ld.shared.u32 %0, [%1];" : "=r"(v) : "r"(a) : "memory"); return v; }
__device__ __forceinline__ uint4 lds128(uint32_t a) {
  uint4 v; asm volatile("ld.shared.v4.u32 {%0,%1,%2,%3}, [%4];" : "=r"(v.x), "=r"(v.y), "=r"(v.z), "=r"(v.w) : "r"(a) : "memory"); return v;
}
__device__ __forceinline__ void poll_ge(const int* p, int target) {
  const uint32_t t0 = clk32();
  while (!__all_sync(0xffffffffu, ld_relaxed(p) >= target)) { __nanosleep(20); if (clk32() - t0 > 0x60000000u) __trap(); }
  fence_acquire();
}

__device__ __forceinline__ uint32_t xn_off(int kb) { return kb == 0 ? OFF_KV : ((kb + 1) & 3) * GSTB + (kb > 4 ? 8192 : 0); }
__device__ __forceinline__ void layernorm_rows(uint4 (&v)[9], uint32_t sb, int r, int grow, bool to_global, int lane) {
  float f[72];
  float s = 0.f;
#pragma unroll
  for (int i = 0; i < 9; i++) {
    f[8 * i] = bf_lo(v[i].x); f[8 * i + 1] = bf_hi(v[i].x); f[8 * i + 2] = bf_lo(v[i].y); f[8 * i + 3] = bf_hi(v[i].y);
    f[8 * i + 4] = bf_lo(v[i].z); f[8 * i + 5] = bf_hi(v[i].z); f[8 * i + 6] = bf_lo(v[i].w); f[8 * i + 7] = bf_hi(v[i].w);
    s += ((f[8 * i] + f[8 * i + 1]) + (f[8 * i + 2] + f[8 * i + 3])) + ((f[8 * i + 4] + f[8 * i + 5]) + (f[8 * i + 6] + f[8 * i + 7]));
  }
#pragma unroll
  for (int o = 4; o; o >>= 1) s += __shfl_xor_sync(0xffffffffu, s, o);
  const float mean = s * (1.f / DM);
  float q0 = 0.f, q1 = 0.f;
#pragma unroll
  for (int i = 0; i < 72; i += 2) { const float a = f[i] - mean, b = f[i + 1] - mean; q0 = fmaf(a, a, q0); q1 = fmaf(b, b, q1); }
  float q = q0 + q1;
#pragma unroll
  for (int o = 4; o; o >>= 1) q += __shfl_xor_sync(0xffffffffu, q, o);
  const float mb = bf_rn(mean);
  const float inv = fdiv(1.f, bf_rn(fsqrt(bf_rn(bf_rn(q * (1.f / DM)) + 1e-5f))));
  auto nrm = [&](int i) { const uint32_t d = pack2(f[i] - mb, f[i + 1] - mb); return pack2(bf_lo(d) * inv, bf_hi(d) * inv); };
  auto halve = [](uint32_t v) { return pack2(bf_lo(v) * 0.5f, bf_hi(v) * 0.5f); };
  uint4* g = reinterpret_cast<uint4*>(g_xn + (size_t)grow * DM) + (lane & 7);
#pragma unroll
  for (int i = 0; i < 9; i++) {
    const uint4 o = make_uint4(nrm(8 * i), nrm(8 * i + 2), nrm(8 * i + 4), nrm(8 * i + 6));
    asm volatile("st.shared.v4.u32 [%0], {%1,%2,%3,%4};" ::"r"(sb + xn_off(i) + r * 128 + (((lane ^ r) & 7) << 4)), "r"(o.x), "r"(o.y), "r"(o.z), "r"(o.w) : "memory");
    if (to_global) g[8 * i] = make_uint4(halve(o.x), halve(o.y), halve(o.z), halve(o.w));
  }
  fence_async_smem();
}

__device__ __forceinline__ void attn_row_slow(int head, int row, int lane) {
  const uint8_t* qp = g_q + (size_t)head * (SEQ * 36) + row * 36;
  float q[18], o[18];
#pragma unroll
  for (int d = 0; d < 18; d += 2) {
    const uint32_t v = __ldcg(reinterpret_cast<const uint32_t*>(qp + d * 2));
    q[d] = bf_lo(v); q[d + 1] = bf_hi(v); o[d] = 0.f; o[d + 1] = 0.f;
  }
  float m = -INFINITY, l = 0.f;
#pragma unroll 1
  for (int key = lane; key < SEQ; key += 32) {
    const uint8_t* kp = g_kv + (size_t)head * (32 * KSTB) + (key >> 3) * 640 + (key & 7) * 16;
    uint32_t wk[9], wv[9];
    auto ld18 = [&](uint32_t (&w)[9], const uint8_t* src, const uint8_t* last) {
      const uint4 a = __ldcg(reinterpret_cast<const uint4*>(src)), b = __ldcg(reinterpret_cast<const uint4*>(src + 128));
      w[0] = a.x; w[1] = a.y; w[2] = a.z; w[3] = a.w; w[4] = b.x; w[5] = b.y; w[6] = b.z; w[7] = b.w;
      w[8] = __ldcg(reinterpret_cast<const uint32_t*>(last));
    };
    ld18(wk, kp, kp + 512); ld18(wv, kp + 256, kp + 520);
    float s = 0.f;
#pragma unroll
    for (int d = 0; d < 9; d++) { s = fmaf(q[2 * d], bf_lo(wk[d]), s); s = fmaf(q[2 * d + 1], bf_hi(wk[d]), s); }
    const float mn = fmaxf(m, s), c = ex2(m - mn), p = ex2(s - mn);
    m = mn; l = l * c + p;
#pragma unroll
    for (int d = 0; d < 9; d++) { o[2 * d] = fmaf(p, bf_lo(wv[d]), o[2 * d] * c); o[2 * d + 1] = fmaf(p, bf_hi(wv[d]), o[2 * d + 1] * c); }
  }
  float M = m;
#pragma unroll
  for (int t = 16; t; t >>= 1) M = fmaxf(M, __shfl_xor_sync(0xffffffffu, M, t));
  const float c = ex2(m - M);
  l *= c;
#pragma unroll
  for (int t = 16; t; t >>= 1) l += __shfl_xor_sync(0xffffffffu, l, t);
  uint32_t* dst = reinterpret_cast<uint32_t*>(g_H + (size_t)row * HW + FF + head * 18);
#pragma unroll
  for (int d = 0; d < 18; d += 2) {
    float a = o[d] * c, b = o[d + 1] * c;
#pragma unroll
    for (int t = 16; t; t >>= 1) { a += __shfl_xor_sync(0xffffffffu, a, t); b += __shfl_xor_sync(0xffffffffu, b, t); }
    if (lane == 0) dst[d >> 1] = pack2(fdiv(a, l), fdiv(b, l));
  }
}

constexpr uint32_t AB = (BH >> 4) + (255u << 16);
template <int MODE>
__device__ __forceinline__ void gemm_run(float (&a0)[96], float (&a1)[96], int nk, int keep, int& st, uint32_t& ph, uint32_t dA,
                                         uint32_t bar_full, int lane) {
  constexpr bool BOTH = MODE == 0;
  uint32_t da = dA + st * (GSTB >> 4);
  uint32_t rel = 0;
  int kb = 0;
  pin(a0); if (BOTH) pin(a1);
#pragma unroll 1
  do {
    wg_fence();
    const uint32_t aa = MODE != 1 ? da : dA + (xn_off(kb) >> 4);
    wgmma_ss_n192(a0, aa, da + AB, kb | keep);
    wg_commit();
    wg_wait<1>();
    if (rel) release_stage(rel, lane);
    if (BOTH) {
      wgmma_ss_n192(a1, da + 512, da + AB, kb | keep);
      wg_commit();
      wg_wait<1>();
    }
    rel = bar_full + 32 + 8 * st;
    if (++st == GST) { st = 0; ph ^= 1; }
    bool ready = false;
#pragma unroll
    for (int k = 1; k < 4; k++) {
      if (k == 3) ready = mbar_test(bar_full + 8 * st, ph);
      wgmma_ss_n192(a0, aa + 2 * k, da + AB + (k >> 1) * (BH2 >> 4) + (k & 1) * 128, 1);
      wg_commit();
      if (BOTH) {
        wg_wait<1>();
        wgmma_ss_n192(a1, da + 512 + 2 * k, da + AB + (k >> 1) * (BH2 >> 4) + (k & 1) * 128, 1);
        wg_commit();
      }
      if (k < 3) wg_wait<1>();
    }
    da = dA + st * (GSTB >> 4);
    if (++kb < nk && !ready) mbar_wait(bar_full + 8 * st, ph);
    wg_wait<1>();
  } while (kb < nk);
  wg_wait<0>();
  pin(a0); if (BOTH) pin(a1);
  release_stage(rel, lane);
}

template <bool ODD>
__device__ __forceinline__ void glu_epilogue(const float (&E)[96], uint32_t s0) {
#pragma unroll
  for (int g = 0; g < 8; g += 2) {
    uint32_t h[4], w[4];
    if (ODD) ldsm4((s0 + 16384) ^ (g << 4), w[0], w[1], w[2], w[3]);
#pragma unroll
    for (int i = 0; i < 4; i++) {
      const int e = 4 * g + 2 * i;
      if (ODD) {
        h[i] = pack2(fmaf(tanhf_fast(E[64 + e]), E[32 + e], E[32 + e]), fmaf(tanhf_fast(E[65 + e]), E[33 + e], E[33 + e]));
        w[i] = pack2(bf_lo(w[i]) * E[e], bf_hi(w[i]) * E[e + 1]);
      } else {
        h[i] = pack2(fmaf(tanhf_fast(E[e]), E[64 + e], E[64 + e]), fmaf(tanhf_fast(E[e + 1]), E[65 + e], E[65 + e]));
        w[i] = pack2(tanhf_fast(E[32 + e]) + 1.f, tanhf_fast(E[33 + e]) + 1.f);
      }
    }
    stsm4(s0 ^ (g << 4), h[0], h[1], h[2], h[3]);
    stsm4((s0 + 16384) ^ (g << 4), w[0], w[1], w[2], w[3]);
  }
}

__device__ __forceinline__ void qkv_scatter(uint32_t tile, int rb, int a, int w, int hoff, int hstep, int lane) {
  const int r8 = lane >> 2, j = lane & 3;
  const int h0 = ((a * 64 * 3641) >> 16) + hoff;
  uint8_t* const qb = g_q + rb * 288 + lane * 4;
  uint8_t* const kb = g_kv + rb * 640 + r8 * 16 + j * 4;
  const uint32_t row = tile + (w * 16 + r8) * 400 + 128;
#pragma unroll 1
  for (int h = h0; h * 18 < a * 64 + 64; h += hstep) {
    uint32_t v[2][4], t[2], q[5];
    bool data[2], qd[5];
    const int col0 = h * 18 - a * 64;
#pragma unroll
    for (int i = 0; i < 5; i++) {
      const int wd = lane + 32 * i, r = (wd * 57) >> 9, col = col0 + 2 * (wd - 9 * r);
      qd[i] = wd < 144 && (unsigned)col < 64u;
      q[i] = lds32(tile + (qd[i] ? (w * 16 + r) * 400 + col * 2 : 0));
    }
#pragma unroll
    for (int c = 0; c < 2; c++) {
      const int col = col0 + c * 8 + 2 * j;
      data[c] = (unsigned)col < 64u;
      const uint32_t src = row + (data[c] ? col : 0) * 2;
#pragma unroll
      for (int e = 0; e < 4; e++) v[c][e] = lds32(src + (e >> 1) * 128 + (e & 1) * 3200);
    }
    const bool tail = (unsigned)(col0 + 16) < 64u;
    const uint32_t ts = row + (tail ? col0 + 16 : 0) * 2 + (j >> 1) * 128;
    t[0] = lds32(ts); t[1] = lds32(ts + 3200);
    if (j & 1) t[0] = t[1] = j == 1 ? 0x3f803f80u : 0u;
    uint8_t* const kp = kb + h * (32 * KSTB);
#pragma unroll
    for (int c = 0; c < 2; c++)
      if (data[c]) {
        *reinterpret_cast<uint32_t*>(kp + c * 128) = v[c][0]; *reinterpret_cast<uint32_t*>(kp + c * 128 + 640) = v[c][1];
        *reinterpret_cast<uint32_t*>(kp + c * 128 + 256) = v[c][2]; *reinterpret_cast<uint32_t*>(kp + c * 128 + 896) = v[c][3];
      }
    if (tail) { *reinterpret_cast<uint32_t*>(kp + 512) = t[0]; *reinterpret_cast<uint32_t*>(kp + 1152) = t[1]; }
    uint8_t* const qp = qb + h * (SEQ * 36);
#pragma unroll
    for (int i = 0; i < 5; i++) if (qd[i]) *reinterpret_cast<uint32_t*>(qp + i * 128) = q[i];
  }
}

__global__ void __cluster_dims__(2, 1, 1) __launch_bounds__(512, 1) fused_kernel(const __grid_constant__ Params P) {
  extern __shared__ __align__(1024) uint8_t smem_raw[];
  const uint32_t sb = (uint32_t)__cvta_generic_to_shared(smem_raw);
  if (sb & 1023u) __trap();
  const uint32_t bar_gfull = sb + OFF_BAR, bar_gempty = bar_gfull + 32;
  const uint32_t bar_kfull = bar_gfull + 256, bar_kempty = bar_kfull + 80;
  const uint32_t bar_gdone = bar_gfull + 160, bar_gfree = bar_gfull + 168, bar_odone = bar_gfull + 176, bar_qdone = bar_gfull + 184, bar_xfree = bar_gfull + 200, bar_q2done = bar_gfull + 208;
  const uint32_t bar_kpeer = bar_kfull + 160;
  const int tid = threadIdx.x;
  const int warp = __shfl_sync(0xffffffffu, tid >> 5, 0);
  const int wg = warp >> 2;
  const int cta = blockIdx.x;
  const bool att = cta < NATT;
  const int cm = cta & 15, cj = cta >> 4;
  const Sched& sch = P.sch[cta];
  const int nq = att ? 2 : 4, ngu = att ? 6 : 0;
  const int qa = att ? cta >> 5 : 8, qrow = att ? (cta & 31) * 64 : (cta - NATT) * 512;

  if (tid == 384) {
    for (int i = 0; i < GST; i++) { mbar_init(bar_gfull + 8 * i, 1); mbar_init(bar_gempty + 8 * i, 8); }
        for (int i = 0; i <= KST; i++) { mbar_init(bar_kfull + 8 * i, 1); mbar_init(bar_kempty + 8 * i, 8); }
    mbar_init(bar_kempty - 8, 8);
    mbar_init(bar_gdone, 4); mbar_init(bar_gfree, 1); mbar_init(bar_odone, 8); mbar_init(bar_qdone, 8); mbar_init(bar_xfree, 4); mbar_init(bar_q2done, 4);
    for (int i = 0; i < KST; i++) mbar_init(bar_kpeer + 8 * i, 1);
    asm volatile("fence.mbarrier_init.release.cluster;" ::: "memory");
    fence_async_smem();
  }
  uint4 xv[9];
  const int lrow = ((warp * 4 + (qa - 1) * 16) & 63) + ((tid & 31) >> 3);
  if (att) {
    const uint4* xr = reinterpret_cast<const uint4*>(P.x + (size_t)(qrow + lrow) * DM) + (tid & 7);
#pragma unroll
    for (int i = 0; i < 9; i++) xv[i] = __ldg(xr + 8 * i);
  }
  if (tid >= 480 && tid < 492) asm volatile("prefetch.tensormap [%0];" ::"l"(&P.xn + (tid - 480)) : "memory");
  __syncwarp();
  cluster_sync();
  const int rank = cta & 1;
  if (warp == 12)
    for (int i = 0; i < GST; i++) {
      expect1(bar_gfull + 8 * i, att ? GSTB - BH : GSTB);
      tma3d_mc(sb + i * GSTB + BH + rank * BH2, &P.wqkv, qa * 64, i * 64 + rank * 32, 0, bar_gfull + 8 * i);
    }
  if (tid == 416 && cm < 10) pf3d(&P.wqkv, qa * 64, GST * 64 + cm * 32, 0);
  if (tid == 448 && att && (cta & 31) < 18) pf3d(&P.wqkv, (qa + 4) * 64, (cta & 31) * 32, 0);
  __syncwarp();
  if (att) {
    layernorm_rows(xv, sb, lrow, qrow + lrow, wg == 1, tid & 31);
    if (wg == 0) bar_sync(4, 512); else bar_arrive(4, 512);
    if (wg == 1) {
      fence_async_glob();
      __syncwarp();
      if ((tid & 31) == 0) { fence_release(); red_relaxed(g_flags + FL_LN + (qrow >> 7) * 32, 4); }
    }
  }

  if (wg == 3) {
    asm volatile("setmaxnreg.dec.sync.aligned.u32 24;");
    const int pw = warp & 3, lane = lane_id();
    const bool el = lane == 0;
    if (pw == 0) {
      int st = 0; uint32_t ph = 1;
      const uint64_t pol = policy_stream();
      auto acquire = [&](uint32_t bytes) -> uint32_t {
        mbar_wait(bar_gempty + 8 * st, ph);
        expect1(bar_gfull + 8 * st, bytes);
        return sb + st * GSTB;
      };
      auto advance = [&]() { if (++st == GST) { st = 0; ph ^= 1; } };
      if (att) {
        ph ^= 1;
#pragma unroll 1
        for (int i = GST; i < 18; i++) {
          const uint32_t s = acquire(GSTB - BH);
          tma3d_mc(s + BH + rank * BH2, &P.wqkv, (i < 9 ? qa : qa + 4) * 64, (i < 9 ? i : i - 9) * 64 + rank * 32, 0, bar_gfull + 8 * st);
          advance();
        }
      } else {
#pragma unroll 1
        for (int t = 0; t < 4; t++) {
          const int row = uni(qrow + t * 128);
          int kb = 0;
          poll_ge(g_flags + FL_LN + (row >> 7) * 32, 128);
          fence_async_glob();
          if (t == 0) {
            for (int i = 0; i < GST; i++) tma2d(sb + i * GSTB, &P.xn, i * 64, row, bar_gfull + 8 * i);
            kb = GST; ph ^= 1;
          }
          st = uni(st); ph = uni(ph); kb = uni(kb);
#pragma unroll 1
          for (; kb < 9; kb++) {
            const uint32_t s = acquire(GSTB);
            tma2d(s, &P.xn, kb * 64, row, bar_gfull + 8 * st);
            tma3d_mc(s + BH + rank * BH2, &P.wqkv, 8 * 64, kb * 64 + rank * 32, 0, bar_gfull + 8 * st);
            advance();
          }
        }
      }
      if (att) { poll_ge(g_flags + FL_LN + cm * 32, 128); fence_async_glob(); }
#pragma unroll 1
      for (int t = 0; t < ngu; t++) {
        const int a0 = uni((cj + 8 * (t >> 1)) * 3), hf = uni(t & 1);
        const CUtensorMap* m2 = hf ? &P.wu2 : &P.wg2; const CUtensorMap* m1 = hf ? &P.wg1 : &P.wu1;
        const int x2 = a0 + hf, x1 = a0 + 2 * hf;
        if (hf && t < 5 && lane < 7) {
          const int b = cm + 16 * lane;
          if (b < 108) pf3d(b < 54 ? &P.wg1 : &P.wu1, 0, ((b % 54) / 3) * 32, a0 + 24 + b % 3);
        }
        if (t == 4 && lane < 4) {
          const int b = cta + 128 * lane;
          if (b < 432) pf3d(&P.wd, 0, (b / 3) * 32, (b % 3) * 3);
          else if (b < 486) pf3d(&P.wo, 0, ((b - 432) / 3) * 32, ((b - 432) % 3) * 3);
        }
        st = uni(st); ph = uni(ph);
#pragma unroll 1
        for (int kb = 0; kb < 9; kb++) {
          const uint32_t s = acquire(GSTB), b = bar_gfull + 8 * st;
          tma2d(s, &P.xn, kb * 64, cm * 128, b);
          tma3d_mc_stream(s + BH + rank * BH2, m2, 0, kb * 64 + rank * 32, x2, b, pol);
          tma3d_mc_stream(s + BH + rank * BH2 + 8192, m1, 0, kb * 64 + rank * 32, x1, b, pol);
          advance();
        }
      }
      auto wait_h = [&](int m, int kb, int k1) -> int {
        const uint32_t t0 = clk32();
        const int i = kb + lane;
        uint32_t b;
        while (true) {
          bool ok = false;
          if (i < k1) ok = ld_relaxed(g_flags + FL_H + m * 96 + i) >= (i < 72 ? 1 : 32 + 8 * (i & 1));
          b = __ballot_sync(0xffffffffu, ok);
          if (b & 1) break;
          __nanosleep(kb >= 78 ? 50 : 200);
          if (clk32() - t0 > 0x60000000u) __trap();
        }
        fence_acquire();
        fence_async_glob();
        return uni(kb + (b == 0xffffffffu ? 32 : __ffs(~b) - 1));
      };
      auto down_range = [&](int m, int n, int k0, int k1) {
#pragma unroll 1
        for (int kb = k0; kb < k1;) {
          const int ready = wait_h(m, kb, k1);
          st = uni(st); ph = uni(ph); kb = uni(kb); m = uni(m); n = uni(n);
          const CUtensorMap* mw = kb < 72 ? &P.wd : &P.wo;
          const int y0 = rank * 32 - (kb < 72 ? 0 : 72 * 64);
#pragma unroll 1
          for (; kb < ready; kb++) {
            const uint32_t s = acquire(GSTB), b = bar_gfull + 8 * st;
            tma2d(s, &P.H, kb * 64, m * 128, b);
            tma3d_mc(s + BH + rank * BH2, mw, 0, kb * 64 + y0, n * 3, b);
            advance();
          }
        }
      };
      const int kind = sch.kind;
#pragma unroll 1
      for (int i = 0; i < sch.nseg; i++) {
        const int va = sch.k0[i], vb = sch.k1[i], ne = sch.kc[i] - NL;
#pragma unroll 1
        for (int h = 0; h < (kind == 1 ? 4 : 2); h++) {
          int k0, k1;
          if (kind == 1) { k0 = h == 0 ? 72 : h == 1 ? ne : h == 2 ? 48 + NL : 76; k1 = h == 0 ? 76 : h == 1 ? 48 : h == 2 ? 72 : 78; }
          else { k0 = h ? (va > ne ? va : ne) + 48 - ne : va; k1 = h ? vb + 48 - ne : (vb < ne ? vb : ne); }
          down_range(sch.m[i], sch.n[i], k0, k1);
        }
      }
      if (kind) {
        const int m = sch.m[0], n = sch.n[0], tile = m * 3 + n, row = m * 128 + (kind - 1) * 64;
        {
          const uint32_t s = acquire(24576);
          for (int c = 0; c < 3; c++) tma2d(s + c * 8192, &P.xin, n * 192 + c * 64, row, bar_gfull + 8 * st);
          advance();
        }
#pragma unroll 1
        for (int p = 0; p < 2; p++) {
          poll_ge(g_flags + FL_P + tile * 3 + p * (3 - kind), 1);
          fence_async_glob();
          const uint32_t s = acquire(24576);
          bulk_load(s, g_part + (tile * 4 + p * 2 + kind - 1) * 1536, 24576, bar_gfull + 8 * st, pol);
          advance();
        }
#pragma unroll 1
        for (int kb = 78; kb < 81;) {
          const int ready = wait_h(m, kb, 81);
          st = uni(st); ph = uni(ph); kb = uni(kb);
#pragma unroll 1
          for (; kb < ready; kb++) {
            const uint32_t s = acquire(GSTB - 8192), b = bar_gfull + 8 * st;
            tma2d(s, &P.H64, kb * 64, row, b);
            tma3d_mc(s + BH + rank * BH2, &P.wo, 0, (kb - 72) * 64 + rank * 32, n * 3, b);
            advance();
          }
        }
      }
    } else if (pw == 1) {
      if (att) {
        const uint64_t pol = policy_stream();
        const uint32_t peer = map_peer(bar_kpeer, rank ^ 1);
        uint32_t st = 0, ph = 0;
        int m = 0;
#pragma unroll 1
        for (int r = 0; r < 5; r++) {
          if (r < 4) {
            const int head = r * 8 + cj, atom = (head * 18 + (lane & 1) * 17) >> 6;
            poll_ge(g_flags + FL_QKV + atom * 32, atom < 8 ? 256 : 128);
            fence_async_glob();
            mbar_wait(bar_kempty + 8 * KST, (r & 1) ^ 1);
            expect1(bar_kfull + 8 * KST, QB);
            bulk_load(sb + OFF_Q, g_q + head * (SEQ * 36) + cm * QB, QB, bar_kfull + 8 * KST, pol);
          }
          if (r == 0) mbar_wait(bar_xfree, 0);
          const int mend = uni(r < 3 ? r * 32 + 27 : (r == 3 ? 0 : 128));
          st = uni(st); ph = uni(ph); m = uni(m);
#pragma unroll 1
          for (; m < mend; m++) {
            mbar_wait(bar_kempty + 8 * st, ph ^ 1);
            expect1(bar_kfull + 8 * st, KSTB);
            if ((m & 1) == rank) {
              mbar_wait(bar_kpeer + 8 * st, ph);
              bulk_load_mc(sb + OFF_KV + st * KSTB, g_kv + (uint32_t)((((m >> 5) * 8 + cj) * 32 + (m & 31)) * KSTB), KSTB, bar_kfull + 8 * st, pol);
            } else arrive_cluster1(peer + 8 * st);
            if (++st == KST) { st = 0; ph ^= 1; }
          }
        }
      }
    } else if (pw == 2) {
      if (att) {
        mbar_wait(bar_qdone, 0);
        mbar_wait(bar_qdone, 1);
        mbar_wait(bar_q2done, 0);
        if (el) { fence_async_glob(); fence_release(); red_relaxed(g_flags + FL_QKV + (qa + 4) * 32, 8); }
        __syncwarp();
      }
      const int nt = ngu + sch.nseg;
#pragma unroll 1
      for (int u = 0; u < nt; u++) {
        mbar_wait(bar_gdone, u & 1);
        if (el) {
          if (u < ngu) {
            const int a0 = (cj + 8 * (u >> 1)) * 3;
            if (u & 1) { tma2d_store(&P.H, (a0 + 1) * 64, cm * 128, sb + OFF_STG + 16384); tma2d_store(&P.H, (a0 + 2) * 64, cm * 128, sb + OFF_STG); }
            else tma2d_store(&P.H, a0 * 64, cm * 128, sb + OFF_STG);
            bulk_commit(); bulk_wait0();
            fence_release();
            if (u & 1) { red_relaxed(g_flags + FL_H + cm * 96 + a0 + 1); red_relaxed(g_flags + FL_H + cm * 96 + a0 + 2); }
            else red_relaxed(g_flags + FL_H + cm * 96 + a0);
          } else {
            fence_async_glob();
            red_release(g_flags + FL_P + (sch.m[u - ngu] * 3 + sch.n[u - ngu]) * 3 + sch.kind);
          }
          mbar_arrive(bar_gfree);
        }
        __syncwarp();
      }
    } else {
      if (att) {
        if (lane < 7) {
          const int b = cm + 16 * lane;
          if (b < 108) pf3d(b < 54 ? &P.wg1 : &P.wu1, 0, ((b % 54) / 3) * 32, cj * 3 + b % 3);
        }
        for (int r = 0; r < 3; r++) {
          mbar_wait(bar_odone, r & 1);
          if (el) {
            const int head = r * 8 + cj, a0 = (head * 18) >> 6, a1 = (head * 18 + 17) >> 6;
            fence_async_glob();
            fence_release();
            red_relaxed(g_flags + FL_H + cm * 96 + 72 + a0, 8);
            if (a1 != a0) red_relaxed(g_flags + FL_H + cm * 96 + 72 + a1, 8);
          }
          __syncwarp();
        }
      }
    }
    if (pw == 0 || (pw == 1 && att)) {
      int old = 0;
      if (el) { __threadfence(); old = atomicAdd(g_flags + FL_DONE, 1); __threadfence(); }
      old = __shfl_sync(0xffffffffu, old, 0);
      if (old == NCTA + NATT - 1) for (int i = lane; i < FL_TOTAL; i += 32) g_flags[i] = 0;
    }
  } else if (wg >= 1) {
    const int lane = lane_id();
#pragma unroll 1
    for (int t = 0; t < nq; t++) {
      bar_sync(1, 384);
      if (att) qkv_scatter(sb + OFF_STG, (qrow >> 3) + (warp & 3) * 2, qa + 4 * t, warp & 3, wg - 1, 2 + t, lane);
      else qkv_scatter(sb + OFF_STG, (qrow >> 3) + t * 16 + (warp - 4) * 2, 8, warp - 4, 0, 1, lane);
      if (att && t) fence_cta(); else fence_async_glob();
      __syncwarp();
      if (lane == 0) {
        if (!att || !t) red_release(g_flags + FL_QKV + qa * 32);
        mbar_arrive(bar_qdone);
      }
    }
    if (att) {
      const int wa = warp - 4;
      const int r8 = lane >> 2, j = lane & 3;
      const uint32_t kvd = __shfl_sync(0xffffffffu, desc_lo(sb + OFF_KV, 0), 0);
      const uint32_t kb0 = __shfl_sync(0xffffffffu, bar_kfull, 0);
      constexpr uint32_t DK = 8u << 16, DK2 = 32, DV = (40u << 16) + 16;
      const uint32_t qa = sb + OFF_Q + (wa * 16 + r8) * 36 + j * 4;
      uint32_t q[8], p[16];
      float s[32], s2[32], o[12];
      auto load_q = [&](int r) {
        mbar_wait(kb0 + 8 * KST, r & 1);
        q[0] = lds32(qa); q[1] = lds32(qa + 288); q[2] = lds32(qa + 16); q[3] = lds32(qa + 304);
        q[4] = j == 0 ? lds32(qa + 32) : 0u; q[5] = j == 0 ? lds32(qa + 320) : 0u; q[6] = 0u; q[7] = 0u;
      };
      load_q(0);
      mbar_wait(kb0, 0);
      pin(q);
      wg_fence();
      wgmma_rs_n64<40, 0>(s, q[0], q[1], q[2], q[3], kvd + DK);
      wgmma_rs_n64<40, 1>(s, q[4], q[5], q[6], q[7], kvd + DK2);
      wg_commit();
      mbar_wait(kb0 + 8, 0);
      wg_wait<0>();
      pin(s);
#pragma unroll
      for (int i = 0; i < 32; i++) s2[i] = 0.f;
#pragma unroll
      for (int i = 0; i < 16; i++) p[i] = 0u;
      uint32_t cur = uni(1), prev = uni(0), old = uni(-1), nph = uni(0);
      auto step = [&](float (&a)[32], float (&b)[32], bool special) {
        const uint32_t d = kvd + cur * (KSTB >> 4);
        const uint32_t nxt = cur + 1 == KST ? 0 : cur + 1;
        nph ^= nxt == 0;
        pin(b); pin(q);
        wg_fence();
        wgmma_rs_n64<40, 0>(b, q[0], q[1], q[2], q[3], d + DK);
        wgmma_rs_n64<40, 1>(b, q[4], q[5], q[6], q[7], d + DK2);
        wg_commit();
#pragma unroll
        for (int i = 0; i < 32; i++) a[i] = ex2(a[i]);
        pin(a);
        wg_wait<1>();
        pin(p); pin(o);
        arrive1(kb0 + 80 + 8 * old);
        const bool ready = mbar_test(kb0 + 8 * nxt, nph);
#pragma unroll
        for (int i = 0; i < 16; i++) p[i] = pack2(a[2 * i], a[2 * i + 1]);
        pin(p);
        wg_fence();
#pragma unroll
        for (int k = 0; k < 4; k++)
          wgmma_rs_n24<8, 1>(o, p[4 * k], p[4 * k + 1], p[4 * k + 2], p[4 * k + 3], kvd + prev * (KSTB >> 4) + DV + k * 80);
        wg_commit();
        if (!ready && !special) mbar_wait(kb0 + 8 * nxt, nph);
        wg_wait<1>();
        pin(b);
        old = prev; prev = cur; cur = nxt;
      };
      auto new_rows = [&]() {
        if (lane == 0) mbar_arrive(kb0 + 80 + 8 * KST);
        {
          float m0 = fmaxf(s[0], s[1]), m1 = fmaxf(s[2], s[3]);
#pragma unroll
          for (int i = 4; i < 32; i += 4) { m0 = fmaxf(m0, fmaxf(s[i], s[i + 1])); m1 = fmaxf(m1, fmaxf(s[i + 2], s[i + 3])); }
          m0 = fmaxf(m0, __shfl_xor_sync(0xffffffffu, m0, 1)); m1 = fmaxf(m1, __shfl_xor_sync(0xffffffffu, m1, 1));
          m0 = fmaxf(m0, __shfl_xor_sync(0xffffffffu, m0, 2)); m1 = fmaxf(m1, __shfl_xor_sync(0xffffffffu, m1, 2));
          m0 = -(m0 + MBIAS); m1 = -(m1 + MBIAS);
          const float h0 = bf_rn(m0), h1 = bf_rn(m1), l0 = bf_rn(m0 - h0), l1 = bf_rn(m1 - h1);
          if (j == 1) { q[4] = pack2(h0, l0); q[5] = pack2(h1, l1); }
          m0 = h0 + l0; m1 = h1 + l1;
#pragma unroll
          for (int i = 0; i < 32; i += 4) { s[i] += m0; s[i + 1] += m0; s[i + 2] += m1; s[i + 3] += m1; }
        }
      };
      new_rows();
#pragma unroll 1
      for (int r = 0; r < 4; r++) {
        const int head = r * 8 + cj;
#pragma unroll
        for (int i = 0; i < 12; i++) o[i] = 0.f;
        const int nq1 = uni(r < 3 ? 15 : -1), nl = uni(r == 3 ? 15 : -1);
        nph = uni(nph);
#pragma unroll 1
        for (int n = uni(0); n < 16; n++) {
          step(s, s2, n == nl);
          if (n == nq1) load_q(r + 1);
          step(s2, s, n == nl);
        }
        if (r < 3) new_rows();
        wg_wait<0>();
        pin(o); pin(s);
        const float l0 = __shfl_sync(0xffffffffu, o[8], (lane & ~3) | 1), l1 = __shfl_sync(0xffffffffu, o[10], (lane & ~3) | 1);
        float lo0 = fminf(fminf(fabsf(o[0]), fabsf(o[1])), fminf(fabsf(o[4]), fabsf(o[5])));
        float lo1 = fminf(fminf(fabsf(o[2]), fabsf(o[3])), fminf(fabsf(o[6]), fabsf(o[7])));
        float z0 = (o[0] + o[1] + o[4] + o[5]) * 0.f, z1 = (o[2] + o[3] + o[6] + o[7]) * 0.f;
        if (j == 2) {
          lo0 = fminf(lo0, fminf(fabsf(o[8]), fabsf(o[9]))); lo1 = fminf(lo1, fminf(fabsf(o[10]), fabsf(o[11])));
          z0 += (o[8] + o[9]) * 0.f; z1 += (o[10] + o[11]) * 0.f;
        }
        const bool ok0 = l0 >= 0x1p-90f && l0 <= 0x1p125f && lo0 >= l0 * 0x1p-33f && z0 == 0.f;
        const bool ok1 = l1 >= 0x1p-90f && l1 <= 0x1p125f && lo1 >= l1 * 0x1p-33f && z1 == 0.f;
        const int row = cm * 128 + wa * 16 + r8;
        {
          const float i0 = fdiv(1.f, l0), i1 = fdiv(1.f, l1);
          uint32_t* d0 = reinterpret_cast<uint32_t*>(g_H + (size_t)row * HW + FF + head * 18) + j;
          uint32_t* d1 = d0 + 8 * (HW / 2);
          d0[0] = pack2(o[0] * i0, o[1] * i0); d0[4] = pack2(o[4] * i0, o[5] * i0);
          d1[0] = pack2(o[2] * i1, o[3] * i1); d1[4] = pack2(o[6] * i1, o[7] * i1);
          if (j == 2) { d0[6] = pack2(o[8] * i0, o[9] * i0); d1[6] = pack2(o[10] * i1, o[11] * i1); }
        }
        const uint32_t bad0 = __ballot_sync(0xffffffffu, !ok0), bad1 = __ballot_sync(0xffffffffu, !ok1);
        if (bad0 | bad1) {
          __syncwarp();
#pragma unroll 1
          for (int rr = 0; rr < 16; rr++)
            if (((rr < 8 ? bad0 : bad1) >> ((rr & 7) * 4)) & 15u) attn_row_slow(head, cm * 128 + wa * 16 + rr, lane);
        }
        if (r < 3) {
          fence_cta();
          __syncwarp();
          if (lane == 0) mbar_arrive(bar_odone);
        } else {
          fence_async_glob();
          __syncwarp();
          if (lane == 0) {
            const int a0 = (head * 18) >> 6, a1 = (head * 18 + 17) >> 6;
            fence_release();
            red_relaxed(g_flags + FL_H + cm * 96 + 72 + a0);
            if (a1 != a0) red_relaxed(g_flags + FL_H + cm * 96 + 72 + a1);
          }
        }
      }
    }
  } else {
    asm volatile("setmaxnreg.inc.sync.aligned.u32 232;");
    const int lane = lane_id();
    float acc0[96], acc1[96];
#pragma unroll
    for (int i = 0; i < 96; i++) asm volatile("" : "=f"(acc0[i]), "=f"(acc1[i]));
    int st = 0; uint32_t ph = 0;
    const uint32_t dA = __shfl_sync(0xffffffffu, desc_lo(sb, 16), 0);
    const uint32_t soff = (warp * 16 + (lane & 15)) * 128 + (((lane >> 4) ^ (lane & 7)) << 4);
#pragma unroll 1
    for (int t = 0; t < nq; t++) {
      mbar_wait(bar_gfull + 8 * st, ph);
      if (att) gemm_run<1>(acc0, acc1, 9, 0, st, ph, dA, bar_gfull, lane);
      else gemm_run<0>(acc0, acc1, 9, 0, st, ph, dA, bar_gfull, lane);
      if (t > 0) {
        if (att && lane == 0) mbar_arrive(bar_xfree);
        mbar_wait(bar_qdone, (t - 1) & 1);
      }
      const float qs = 0.23570226039551584f * 1.4426950408889634f;
      const float xs = att ? 1.f : 2.f;
      auto st_qkv = [&](float (&acc)[96], uint32_t pa) {
#pragma unroll
        for (int g = 0; g < 24; g += 2) {
          const float f = g < 8 ? qs * xs : xs;
          stsm4(pa + g * 16, pack2(acc[4 * g] * f, acc[4 * g + 1] * f), pack2(acc[4 * g + 2] * f, acc[4 * g + 3] * f),
                pack2(acc[4 * g + 4] * f, acc[4 * g + 5] * f), pack2(acc[4 * g + 6] * f, acc[4 * g + 7] * f));
        }
      };
      const uint32_t pa = sb + OFF_STG + (warp * 16 + (lane & 15)) * 400 + (lane >> 4) * 16;
      st_qkv(acc0, pa);
      if (!att) st_qkv(acc1, pa + 64 * 400);
      bar_arrive(1, 384);
      if (att && t) {
        __syncwarp();
        qkv_scatter(sb + OFF_STG, (qrow >> 3) + warp * 2, qa + 4, warp, 2, 3, lane);
        fence_cta();
        __syncwarp();
        if (lane == 0) mbar_arrive(bar_q2done);
      }
    }
#pragma unroll 1
    for (int u = 0; u < ngu; u++) {
      mbar_wait(bar_gfull + 8 * st, ph);
      gemm_run<0>(acc0, acc1, 9, 0, st, ph, dA, bar_gfull, lane);
      if (u) mbar_wait(bar_gfree, (u - 1) & 1); else mbar_wait(bar_qdone, 1);
      const uint32_t s4 = sb + OFF_STG + soff;
      if (u & 1) { glu_epilogue<true>(acc0, s4); glu_epilogue<true>(acc1, s4 + 8192); }
      else { glu_epilogue<false>(acc0, s4); glu_epilogue<false>(acc1, s4 + 8192); }
      fence_async_smem();
      __syncwarp();
      if (lane == 0) mbar_arrive(bar_gdone);
    }
    const int kind = sch.kind;
#pragma unroll 1
    for (int sg = 0; sg < sch.nseg; sg++) {
      mbar_wait(bar_gfull + 8 * st, ph);
      gemm_run<0>(acc0, acc1, kind == 1 ? 78 - sch.kc[0] : sch.k1[sg] - sch.k0[sg], 0, st, ph, dA, bar_gfull, lane);
      uint4* pp = g_part + ((sch.m[sg] * 3 + sch.n[sg]) * 4 + (kind ? 2 : 0)) * 1536 + warp * 32 + lane;
      auto put = [&](const float (&acc)[96], uint4* q) {
#pragma unroll
        for (int i = 0; i < 12; i++)
          q[i * 128] = make_uint4(pack2(acc[8 * i], acc[8 * i + 1]), pack2(acc[8 * i + 2], acc[8 * i + 3]),
                                  pack2(acc[8 * i + 4], acc[8 * i + 5]), pack2(acc[8 * i + 6], acc[8 * i + 7]));
      };
      if (kind != 1) put(acc0, pp);
      if (kind != 2) put(acc1, pp + 1536);
      fence_cta();
      if (ngu + sg) mbar_wait(bar_gfree, (ngu + sg - 1) & 1);
      __syncwarp();
      if (lane == 0) mbar_arrive(bar_gdone);
    }
    if (kind) {
      if (kind == 2) {
#pragma unroll
        for (int i = 0; i < 96; i++) acc0[i] = acc1[i];
      }
      {
        mbar_wait(bar_gfull + 8 * st, ph);
        uint32_t dep = 0;
#pragma unroll
        for (int g = 0; g < 24; g += 2) {
          uint32_t w[4];
          ldsm4((sb + st * GSTB + (g >> 3) * 8192 + soff) ^ ((g & 7) << 4), w[0], w[1], w[2], w[3]);
          dep |= w[3];
#pragma unroll
          for (int i = 0; i < 4; i++) { acc0[4 * g + 2 * i] += bf_lo(w[i]); acc0[4 * g + 2 * i + 1] += bf_hi(w[i]); }
        }
        release_stage(bar_gempty + 8 * st + (dep & P.zero), lane);
        if (++st == GST) { st = 0; ph ^= 1; }
      }
#pragma unroll 1
      for (int pp = 0; pp < 2; pp++) {
        mbar_wait(bar_gfull + 8 * st, ph);
        const uint32_t a = sb + st * GSTB + (warp * 32 + lane) * 16;
        uint32_t dep = 0;
#pragma unroll
        for (int i = 0; i < 12; i++) {
          const uint4 v = lds128(a + i * 2048);
          dep |= v.w;
          acc0[8 * i] += bf_lo(v.x); acc0[8 * i + 1] += bf_hi(v.x); acc0[8 * i + 2] += bf_lo(v.y); acc0[8 * i + 3] += bf_hi(v.y);
          acc0[8 * i + 4] += bf_lo(v.z); acc0[8 * i + 5] += bf_hi(v.z); acc0[8 * i + 6] += bf_lo(v.w); acc0[8 * i + 7] += bf_hi(v.w);
        }
        release_stage(bar_gempty + 8 * st + (dep & P.zero), lane);
        if (++st == GST) { st = 0; ph ^= 1; }
      }
      mbar_wait(bar_gfull + 8 * st, ph);
      gemm_run<2>(acc0, acc1, 3, 1, st, ph, dA, bar_gfull, lane);
#pragma unroll
      for (int g = 0; g < 24; g += 2)
        stsm4((sb + OFF_STG + (g >> 3) * 8192 + soff) ^ ((g & 7) << 4), pack2(acc0[4 * g], acc0[4 * g + 1]), pack2(acc0[4 * g + 2], acc0[4 * g + 3]),
              pack2(acc0[4 * g + 4], acc0[4 * g + 5]), pack2(acc0[4 * g + 6], acc0[4 * g + 7]));
      fence_async_smem();
      bar_sync(12, 128);
      if (warp == 0 && lane == 0) {
        for (int a = 0; a < 3; a++) tma2d_store(&P.out, sch.n[0] * 192 + a * 64, sch.m[0] * 128 + (kind - 1) * 64, sb + OFF_STG + a * 8192);
        bulk_commit(); bulk_wait0();
      }
    }
  }
  __syncwarp();
  cluster_sync();
}

typedef CUresult (*EncodeFn)(CUtensorMap*, CUtensorMapDataType, cuuint32_t, void*, const cuuint64_t*, const cuuint64_t*, const cuuint32_t*,
                             const cuuint32_t*, CUtensorMapInterleave, CUtensorMapSwizzle, CUtensorMapL2promotion, CUtensorMapFloatOOBfill);

void make_map(EncodeFn enc, CUtensorMap* m, const void* ptr, int rank, uint64_t d0, uint64_t d1, uint64_t d2, uint64_t s1, uint64_t s2,
              uint32_t b0, uint32_t b1, uint32_t b2) {
  cuuint64_t gd[3] = {d0, d1, d2}, gs[2] = {s1, s2};
  cuuint32_t bd[3] = {b0, b1, b2}, es[3] = {1, 1, 1};
  enc(m, CU_TENSOR_MAP_DATA_TYPE_BFLOAT16, rank, const_cast<void*>(ptr), gd, gs, bd, es, CU_TENSOR_MAP_INTERLEAVE_NONE,
      CU_TENSOR_MAP_SWIZZLE_128B, CU_TENSOR_MAP_L2_PROMOTION_L2_128B, CU_TENSOR_MAP_FLOAT_OOB_FILL_NONE);
}

void build_schedule(Sched* s) {
  for (int i = 0; i < NCTA; i++) s[i] = Sched{};
  auto add = [&](int pair, int kind, int tp, int k0, int k1, int kc) {
    for (int r = 0; r < 2; r++) {
      Sched& c = s[2 * pair + r];
      c.kind = kind; c.m[c.nseg] = 2 * (tp / 3) + r; c.n[c.nseg] = tp % 3; c.k0[c.nseg] = k0; c.k1[c.nseg] = k1; c.kc[c.nseg] = kc; c.nseg++;
    }
  };
  for (int t = 0; t < 24; t++) {
    const int c = t < 8 ? CF : C1, kc = c + (t < 8 ? C3 : C2);
    add(t < 8 ? 64 + t / 4 : 40 + t, 0, t, 0, c, kc);
    add(t, 1, t, 0, 0, kc);
    add(24 + t, 2, t, c, kc, kc);
  }
}

}

extern "C" void kernel_launch(void* const* d_in, const int* in_sizes, int n_in, void* d_out, int out_size) {
  static EncodeFn enc = nullptr;
  if (!enc) {
    void* f = nullptr; cudaDriverEntryPointQueryResult q;
    cudaGetDriverEntryPoint("cuTensorMapEncodeTiled", &f, cudaEnableDefault, &q);
    enc = (EncodeFn)f;
    cudaFuncSetAttribute(fused_kernel, cudaFuncAttributeMaxDynamicSharedMemorySize, SMEM_BYTES);
  }
  void *xn, *H;
  cudaGetSymbolAddress(&xn, g_xn);
  cudaGetSymbolAddress(&H, g_H);
  Params P;
  P.x = (const __nv_bfloat16*)d_in[0];
  P.zero = 0; P.pad = 0;
  make_map(enc, &P.xn, xn, 2, DM, SEQ, 1, DM * 2, 0, 64, 128, 1);
  make_map(enc, &P.xin, d_in[0], 2, DM, SEQ, 1, DM * 2, 0, 64, 64, 1);
  make_map(enc, &P.H64, H, 2, HW, SEQ, 1, HW * 2, 0, 64, 64, 1);
  make_map(enc, &P.H, H, 2, HW, SEQ, 1, HW * 2, 0, 64, 128, 1);
  make_map(enc, &P.out, d_out, 2, DM, SEQ, 1, DM * 2, 0, 64, 64, 1);
  make_map(enc, &P.wqkv, d_in[1], 3, DM, DM, 3, 3 * DM * 2, DM * 2, 64, 32, 3);
  make_map(enc, &P.wg1, d_in[4], 3, 64, DM, 72, FF * 2, 128, 64, 32, 1);
  make_map(enc, &P.wu1, d_in[5], 3, 64, DM, 72, FF * 2, 128, 64, 32, 1);
  make_map(enc, &P.wg2, d_in[4], 3, 64, DM, 72, FF * 2, 128, 64, 32, 2);
  make_map(enc, &P.wu2, d_in[5], 3, 64, DM, 72, FF * 2, 128, 64, 32, 2);
  make_map(enc, &P.wd, d_in[6], 3, 64, FF, 9, DM * 2, 128, 64, 32, 3);
  make_map(enc, &P.wo, d_in[2], 3, 64, DM, 9, DM * 2, 128, 64, 32, 3);
  build_schedule(P.sch);
  fused_kernel<<<NCTA, 512, SMEM_BYTES>>>(P);
}
```

```cpp
#include <cuda_runtime.h>
#include <cuda_bf16.h>
#include <cuda.h>
#include <stdint.h>

__device__ __forceinline__ void wgmma_ss_n192(float (&d)[96], uint32_t alo, uint32_t blo, int sd) {
  asm volatile("{\n.reg .pred p;\n.reg .b64 da, db;\nsetp.ne.b32 p, %98, 0;\nmov.b64 da, {%96, 0x40000040};\nmov.b64 db, {%97, 0x40000040};\n"
    "wgmma.mma_async.sync.aligned.m64n192k16.f32.bf16.bf16 {%0, %1, %2, %3, %4, %5, %6, %7, %8, %9, %10, %11, %12, %13, %14, %15, %16, %17, %18, %19, %20, %21, %22, %23, %24, %25, %26, %27, %28, %29, %30, %31, %32, %33, %34, %35, %36, %37, %38, %39, %40, %41, %42, %43, %44, %45, %46, %47, %48, %49, %50, %51, %52, %53, %54, %55, %56, %57, %58, %59, %60, %61, %62, %63, %64, %65, %66, %67, %68, %69, %70, %71, %72, %73, %74, %75, %76, %77, %78, %79, %80, %81, %82, %83, %84, %85, %86, %87, %88, %89, %90, %91, %92, %93, %94, %95}, da, db, p, 1, 1, 0, 1;\n}\n"
    : "+f"(d[0]), "+f"(d[1]), "+f"(d[2]), "+f"(d[3]), "+f"(d[4]), "+f"(d[5]), "+f"(d[6]), "+f"(d[7]), "+f"(d[8]), "+f"(d[9]), "+f"(d[10]), "+f"(d[11]), "+f"(d[12]), "+f"(d[13]), "+f"(d[14]), "+f"(d[15]), "+f"(d[16]), "+f"(d[17]), "+f"(d[18]), "+f"(d[19]), "+f"(d[20]), "+f"(d[21]), "+f"(d[22]), "+f"(d[23]), "+f"(d[24]), "+f"(d[25]), "+f"(d[26]), "+f"(d[27]), "+f"(d[28]), "+f"(d[29]), "+f"(d[30]), "+f"(d[31]), "+f"(d[32]), "+f"(d[33]), "+f"(d[34]), "+f"(d[35]), "+f"(d[36]), "+f"(d[37]), "+f"(d[38]), "+f"(d[39]), "+f"(d[40]), "+f"(d[41]), "+f"(d[42]), "+f"(d[43]), "+f"(d[44]), "+f"(d[45]), "+f"(d[46]), "+f"(d[47]), "+f"(d[48]), "+f"(d[49]), "+f"(d[50]), "+f"(d[51]), "+f"(d[52]), "+f"(d[53]), "+f"(d[54]), "+f"(d[55]), "+f"(d[56]), "+f"(d[57]), "+f"(d[58]), "+f"(d[59]), "+f"(d[60]), "+f"(d[61]), "+f"(d[62]), "+f"(d[63]), "+f"(d[64]), "+f"(d[65]), "+f"(d[66]), "+f"(d[67]), "+f"(d[68]), "+f"(d[69]), "+f"(d[70]), "+f"(d[71]), "+f"(d[72]), "+f"(d[73]), "+f"(d[74]), "+f"(d[75]), "+f"(d[76]), "+f"(d[77]), "+f"(d[78]), "+f"(d[79]), "+f"(d[80]), "+f"(d[81]), "+f"(d[82]), "+f"(d[83]), "+f"(d[84]), "+f"(d[85]), "+f"(d[86]), "+f"(d[87]), "+f"(d[88]), "+f"(d[89]), "+f"(d[90]), "+f"(d[91]), "+f"(d[92]), "+f"(d[93]), "+f"(d[94]), "+f"(d[95])
    : "r"(alo), "r"(blo), "r"(sd));
}
template <uint32_t BHI, int SD> __device__ __forceinline__ void wgmma_rs_n64(float (&d)[32], uint32_t a0, uint32_t a1, uint32_t a2, uint32_t a3, uint32_t blo) {
  asm volatile("{\n.reg .b64 db;\nmov.b64 db, {%36, %37};\n"
    "wgmma.mma_async.sync.aligned.m64n64k16.f32.bf16.bf16 {%0, %1, %2, %3, %4, %5, %6, %7, %8, %9, %10, %11, %12, %13, %14, %15, %16, %17, %18, %19, %20, %21, %22, %23, %24, %25, %26, %27, %28, %29, %30, %31}, {%32,%33,%34,%35}, db, %38, 1, 1, 0;\n}\n"
    : "+f"(d[0]), "+f"(d[1]), "+f"(d[2]), "+f"(d[3]), "+f"(d[4]), "+f"(d[5]), "+f"(d[6]), "+f"(d[7]), "+f"(d[8]), "+f"(d[9]), "+f"(d[10]), "+f"(d[11]), "+f"(d[12]), "+f"(d[13]), "+f"(d[14]), "+f"(d[15]), "+f"(d[16]), "+f"(d[17]), "+f"(d[18]), "+f"(d[19]), "+f"(d[20]), "+f"(d[21]), "+f"(d[22]), "+f"(d[23]), "+f"(d[24]), "+f"(d[25]), "+f"(d[26]), "+f"(d[27]), "+f"(d[28]), "+f"(d[29]), "+f"(d[30]), "+f"(d[31])
    : "r"(a0), "r"(a1), "r"(a2), "r"(a3), "r"(blo), "n"(BHI), "n"(SD));
}
template <uint32_t BHI, int SD> __device__ __forceinline__ void wgmma_rs_n24(float (&d)[12], uint32_t a0, uint32_t a1, uint32_t a2, uint32_t a3, uint32_t blo) {
  asm volatile("{\n.reg .b64 db;\nmov.b64 db, {%16, %17};\n"
    "wgmma.mma_async.sync.aligned.m64n24k16.f32.bf16.bf16 {%0, %1, %2, %3, %4, %5, %6, %7, %8, %9, %10, %11}, {%12,%13,%14,%15}, db, %18, 1, 1, 1;\n}\n"
    : "+f"(d[0]), "+f"(d[1]), "+f"(d[2]), "+f"(d[3]), "+f"(d[4]), "+f"(d[5]), "+f"(d[6]), "+f"(d[7]), "+f"(d[8]), "+f"(d[9]), "+f"(d[10]), "+f"(d[11])
    : "r"(a0), "r"(a1), "r"(a2), "r"(a3), "r"(blo), "n"(BHI), "n"(SD));
}

#define GP(...) __VA_ARGS__
#define HINT "20000"
#define PSLEEP 20
#define LSLEEP 50
namespace {

constexpr int SEQ = 2048, DM = 576, FF = 4608, HW = FF + DM;
constexpr int NCTA = 132, NATT = 128;
#define P_C1 26
#define P_C2 26
#define P_C3 28
#define P_F 22
constexpr int NL = 8, C1 = P_C1, C2 = P_C2, C3 = P_C3, CF = P_F;
constexpr int GST = 4, GSTB = 40960;
constexpr int KST = 6, KSTB = 5120;
constexpr int QB = 128 * 36;
constexpr int OFF_STG = GST * GSTB;
constexpr int OFF_KV = OFF_STG + 32768;
constexpr int OFF_Q = OFF_KV + KST * KSTB;
constexpr int OFF_BAR = OFF_Q + QB;
constexpr int SMEM_BYTES = OFF_BAR + 512;
constexpr int BH = 16384, BH2 = 12288;
constexpr float MBIAS = 72.f;

constexpr int FL_LN = 0;
constexpr int FL_QKV = 512;
constexpr int FL_H = 1024;
constexpr int FL_P = FL_H + 16 * 96;
constexpr int FL_DONE = FL_P + 48 * 3;
constexpr int FL_TOTAL = FL_DONE + 32;

struct Sched { uint8_t nseg, kind, m[4], n[4], k0[4], k1[4], kc[4], pad[2]; };
struct Params {
  CUtensorMap xn, H, H64, out, wqkv, wg1, wu1, wg2, wu2, wd, wo, xin;
  const __nv_bfloat16* x;
  uint32_t zero, pad;
  Sched sch[NCTA];
};

__device__ __align__(1024) __nv_bfloat16 g_xn[SEQ * DM];
__device__ __align__(1024) __nv_bfloat16 g_H[SEQ * HW];
__device__ __align__(1024) uint8_t g_q[32 * SEQ * 36];
__device__ __align__(1024) uint8_t g_kv[32 * 32 * KSTB];
__device__ __align__(1024) uint4 g_part[48 * 4 * 1536];
__device__ int g_flags[FL_TOTAL];
#define STAMP(i)
#define TIC(v)
#define TOC(acc, v)
#define PUT(i, val)

__device__ __forceinline__ void wg_fence() { asm volatile("wgmma.fence.sync.aligned;" ::: "memory"); }
__device__ __forceinline__ void wg_commit() { asm volatile("wgmma.commit_group.sync.aligned;" ::: "memory"); }
template <int N> __device__ __forceinline__ void wg_wait() { asm volatile("wgmma.wait_group.sync.aligned %0;" ::"n"(N) : "memory"); }
template <int N> __device__ __forceinline__ void pin(float (&d)[N]) {
#pragma unroll
  for (int i = 0; i < N; i++) asm volatile("" : "+f"(d[i])::"memory");
}
template <int N> __device__ __forceinline__ void pin(uint32_t (&d)[N]) {
#pragma unroll
  for (int i = 0; i < N; i++) asm volatile("" : "+r"(d[i])::"memory");
}
__device__ __forceinline__ uint32_t desc_lo(uint32_t addr, uint32_t lbo) { return ((addr & 0x3FFFF) >> 4) | ((lbo >> 4) << 16); }
__device__ __forceinline__ float ex2(float x) { float r; asm("ex2.approx.ftz.f32 %0, %1;" : "=f"(r) : "f"(x)); return r; }
__device__ __forceinline__ float tanhf_fast(float x) { float r; asm("tanh.approx.f32 %0, %1;" : "=f"(r) : "f"(x)); return r; }
__device__ __forceinline__ uint32_t pack2(float lo, float hi) { uint32_t r; asm("cvt.rn.bf16x2.f32 %0, %1, %2;" : "=r"(r) : "f"(hi), "f"(lo)); return r; }
__device__ __forceinline__ float bf_lo(uint32_t v) { float r; asm("shl.b32 %0, %1, 16;" : "=f"(r) : "r"(v)); return r; }
__device__ __forceinline__ float bf_hi(uint32_t v) { float r; asm("and.b32 %0, %1, 0xffff0000;" : "=f"(r) : "r"(v)); return r; }
__device__ __forceinline__ float bf_rn(float v) { return __bfloat162float(__float2bfloat16_rn(v)); }
__device__ __forceinline__ float fdiv(float a, float b) { float r; asm("div.full.f32 %0, %1, %2;" : "=f"(r) : "f"(a), "f"(b)); return r; }
__device__ __forceinline__ float fsqrt(float a) { float r; asm("sqrt.approx.f32 %0, %1;" : "=f"(r) : "f"(a)); return r; }
__device__ __forceinline__ int lane_id() { int l; asm volatile("mov.u32 %0, %%laneid;" : "=r"(l)); return l; }
__device__ __forceinline__ uint32_t clk32() { uint32_t c; asm volatile("mov.u32 %0, %%clock;" : "=r"(c)); return c; }

__device__ __forceinline__ void mbar_init(uint32_t a, uint32_t c) { asm volatile("mbarrier.init.shared::cta.b64 [%0], %1;" ::"r"(a), "r"(c) : "memory"); }
__device__ __forceinline__ void mbar_arrive(uint32_t a) { asm volatile("mbarrier.arrive.shared::cta.b64 _, [%0];" ::"r"(a) : "memory"); }
__device__ __forceinline__ bool mbar_test(uint32_t a, uint32_t ph) {
  uint32_t ok;
  asm volatile("{\n.reg .pred p;\nmbarrier.test_wait.parity.shared::cta.b64 p, [%1], %2;\nselp.u32 %0, 1, 0, p;\n}\n" : "=r"(ok) : "r"(a), "r"(ph) : "memory");
  return ok;
}
__device__ __forceinline__ void mbar_wait(uint32_t a, uint32_t ph) {
  asm volatile("{\n.reg .pred p;\n.reg .u32 n;\nmbarrier.try_wait.parity.shared::cta.b64 p, [%0], %1;\n@p bra D_%=;\nmov.u32 n, 0;\n"
               "W_%=:\nmbarrier.try_wait.parity.shared::cta.b64 p, [%0], %1, " HINT ";\n@p bra D_%=;\n"
               "add.u32 n, n, 1;\nsetp.lt.u32 p, n, 200000;\n@p bra W_%=;\ntrap;\nD_%=:\n}\n" ::"r"(a), "r"(ph) : "memory");
}
#define ELECT "{\n.reg .pred e;\nelect.sync _|e, 0xffffffff;\n@e "
__device__ __forceinline__ uint64_t policy_stream() {
  uint64_t p; asm("createpolicy.fractional.L2::evict_first.b64 %0, 1.0;" : "=l"(p)); return p;
}
__device__ __forceinline__ void expect1(uint32_t a, uint32_t b) { asm volatile(ELECT "mbarrier.arrive.expect_tx.shared::cta.b64 _, [%0], %1;\n}\n" ::"r"(a), "r"(b) : "memory"); }
__device__ __forceinline__ void arrive1(uint32_t a) { asm volatile(ELECT "mbarrier.arrive.shared::cta.b64 _, [%0];\n}\n" ::"r"(a) : "memory"); }
__device__ __forceinline__ void tma2d(uint32_t dst, const CUtensorMap* m, int c0, int c1, uint32_t bar) {
  asm volatile(ELECT "cp.async.bulk.tensor.2d.shared::cluster.global.mbarrier::complete_tx::bytes [%0], [%1, {%3, %4}], [%2];\n}\n"
               ::"r"(dst), "l"(m), "r"(bar), "r"(c0), "r"(c1) : "memory");
}
__device__ __forceinline__ void tma3d_mc(uint32_t dst, const CUtensorMap* m, int c0, int c1, int c2, uint32_t bar) {
  asm volatile(ELECT "cp.async.bulk.tensor.3d.shared::cluster.global.mbarrier::complete_tx::bytes.multicast::cluster [%0], [%1, {%3, %4, %5}], [%2], %6;\n}\n"
               ::"r"(dst), "l"(m), "r"(bar), "r"(c0), "r"(c1), "r"(c2), "h"((uint16_t)3) : "memory");
}
__device__ __forceinline__ void tma3d_mc_stream(uint32_t dst, const CUtensorMap* m, int c0, int c1, int c2, uint32_t bar, uint64_t pol) {
  asm volatile(ELECT "cp.async.bulk.tensor.3d.shared::cluster.global.mbarrier::complete_tx::bytes.multicast::cluster.L2::cache_hint [%0], [%1, {%3, %4, %5}], [%2], %6, %7;\n}\n"
               ::"r"(dst), "l"(m), "r"(bar), "r"(c0), "r"(c1), "r"(c2), "h"((uint16_t)3), "l"(pol) : "memory");
}
__device__ __forceinline__ void bulk_load(uint32_t dst, const void* src, uint32_t bytes, uint32_t bar, uint64_t pol) {
  asm volatile(ELECT "cp.async.bulk.shared::cluster.global.mbarrier::complete_tx::bytes.L2::cache_hint [%0], [%1], %2, [%3], %4;\n}\n"
               ::"r"(dst), "l"(src), "r"(bytes), "r"(bar), "l"(pol) : "memory");
}
__device__ __forceinline__ void bulk_load_mc(uint32_t dst, const void* src, uint32_t bytes, uint32_t bar, uint64_t pol) {
  asm volatile(ELECT "cp.async.bulk.shared::cluster.global.mbarrier::complete_tx::bytes.multicast::cluster.L2::cache_hint [%0], [%1], %2, [%3], %4, %5;\n}\n"
               ::"r"(dst), "l"(src), "r"(bytes), "r"(bar), "h"((uint16_t)3), "l"(pol) : "memory");
}
__device__ __forceinline__ uint32_t map_peer(uint32_t a, uint32_t rank) { uint32_t r; asm("mapa.shared::cluster.u32 %0, %1, %2;" : "=r"(r) : "r"(a), "r"(rank)); return r; }
__device__ __forceinline__ void arrive_cluster(uint32_t a) { asm volatile("mbarrier.arrive.relaxed.cluster.shared::cluster.b64 _, [%0];" ::"r"(a) : "memory"); }
__device__ __forceinline__ void arrive_cluster1(uint32_t a) { asm volatile(ELECT "mbarrier.arrive.relaxed.cluster.shared::cluster.b64 _, [%0];\n}\n" ::"r"(a) : "memory"); }
__device__ __forceinline__ void release_stage(uint32_t a, int lane) { if (lane < 2) arrive_cluster(map_peer(a, lane)); }
__device__ __forceinline__ void cluster_sync() { asm volatile("barrier.cluster.arrive.relaxed.aligned;\nbarrier.cluster.wait.aligned;" ::: "memory"); }
__device__ __forceinline__ int uni(int v) { return __shfl_sync(0xffffffffu, v, 0); }
__device__ __forceinline__ void tma2d_store(const CUtensorMap* m, int c0, int c1, uint32_t src) {
  asm volatile("cp.async.bulk.tensor.2d.global.shared::cta.bulk_group [%0, {%2, %3}], [%1];" ::"l"(m), "r"(src), "r"(c0), "r"(c1) : "memory");
}
__device__ __forceinline__ void pf3d(const CUtensorMap* m, int c0, int c1, int c2) {
  asm volatile("cp.async.bulk.prefetch.tensor.3d.L2.global [%0, {%1, %2, %3}];" ::"l"(m), "r"(c0), "r"(c1), "r"(c2) : "memory");
}
__device__ __forceinline__ void bulk_commit() { asm volatile("cp.async.bulk.commit_group;" ::: "memory"); }
__device__ __forceinline__ void bulk_wait0() { asm volatile("cp.async.bulk.wait_group 0;" ::: "memory"); }
__device__ __forceinline__ void fence_async_glob() { asm volatile("fence.proxy.async.global;" ::: "memory"); }
__device__ __forceinline__ void fence_cta() { asm volatile("fence.acq_rel.cta;" ::: "memory"); }
__device__ __forceinline__ void fence_release() { asm volatile("fence.release.gpu;" ::: "memory"); }
__device__ __forceinline__ void red_relaxed(int* p, int v = 1) { asm volatile("red.relaxed.gpu.global.add.s32 [%0], %1;" ::"l"(p), "r"(v) : "memory"); }
__device__ __forceinline__ void bar_arrive(int id, int n) { asm volatile("bar.arrive %0, %1;" ::"r"(id), "r"(n) : "memory"); }
__device__ __forceinline__ void bar_sync(int id, int n) { asm volatile("bar.sync %0, %1;" ::"r"(id), "r"(n) : "memory"); }
__device__ __forceinline__ void fence_async_smem() { asm volatile("fence.proxy.async.shared::cta;" ::: "memory"); }
__device__ __forceinline__ void red_release(int* p) { asm volatile("red.release.gpu.global.add.s32 [%0], 1;" ::"l"(p) : "memory"); }
__device__ __forceinline__ int ld_relaxed(const int* p) { int v; asm volatile("ld.relaxed.gpu.global.s32 %0, [%1];" : "=r"(v) : "l"(p) : "memory"); return v; }
__device__ __forceinline__ void fence_acquire() { asm volatile("fence.acquire.gpu;" ::: "memory"); }
__device__ __forceinline__ void stsm4(uint32_t a, uint32_t r0, uint32_t r1, uint32_t r2, uint32_t r3) {
  asm volatile("stmatrix.sync.aligned.m8n8.x4.shared.b16 [%0], {%1,%2,%3,%4};" ::"r"(a), "r"(r0), "r"(r1), "r"(r2), "r"(r3) : "memory");
}
__device__ __forceinline__ void ldsm4(uint32_t a, uint32_t& r0, uint32_t& r1, uint32_t& r2, uint32_t& r3) {
  asm volatile("ldmatrix.sync.aligned.m8n8.x4.shared.b16 {%0,%1,%2,%3}, [%4];" : "=r"(r0), "=r"(r1), "=r"(r2), "=r"(r3) : "r"(a) : "memory");
}
__device__ __forceinline__ uint32_t lds32(uint32_t a) { uint32_t v; asm volatile("ld.shared.u32 %0, [%1];" : "=r"(v) : "r"(a) : "memory"); return v; }
__device__ __forceinline__ uint4 lds128(uint32_t a) {
  uint4 v; asm volatile("ld.shared.v4.u32 {%0,%1,%2,%3}, [%4];" : "=r"(v.x), "=r"(v.y), "=r"(v.z), "=r"(v.w) : "r"(a) : "memory"); return v;
}
__device__ __forceinline__ void poll_ge(const int* p, int target) {
  const uint32_t t0 = clk32();
  while (!__all_sync(0xffffffffu, ld_relaxed(p) >= target)) { __nanosleep(PSLEEP); if (clk32() - t0 > 0x60000000u) __trap(); }
  fence_acquire();
}

__device__ __forceinline__ uint32_t xn_off(int kb) { return kb == 0 ? OFF_KV : ((kb + 1) & 3) * GSTB + (kb > 4 ? 8192 : 0); }
__device__ __forceinline__ void layernorm_rows(uint4 (&v)[9], uint32_t sb, int r, int grow, bool to_global, int lane) {
  float f[72];
  float s = 0.f;
#pragma unroll
  for (int i = 0; i < 9; i++) {
    f[8 * i] = bf_lo(v[i].x); f[8 * i + 1] = bf_hi(v[i].x); f[8 * i + 2] = bf_lo(v[i].y); f[8 * i + 3] = bf_hi(v[i].y);
    f[8 * i + 4] = bf_lo(v[i].z); f[8 * i + 5] = bf_hi(v[i].z); f[8 * i + 6] = bf_lo(v[i].w); f[8 * i + 7] = bf_hi(v[i].w);
    s += ((f[8 * i] + f[8 * i + 1]) + (f[8 * i + 2] + f[8 * i + 3])) + ((f[8 * i + 4] + f[8 * i + 5]) + (f[8 * i + 6] + f[8 * i + 7]));
  }
#pragma unroll
  for (int o = 4; o; o >>= 1) s += __shfl_xor_sync(0xffffffffu, s, o);
  const float mean = s * (1.f / DM);
  float q0 = 0.f, q1 = 0.f;
#pragma unroll
  for (int i = 0; i < 72; i += 2) { const float a = f[i] - mean, b = f[i + 1] - mean; q0 = fmaf(a, a, q0); q1 = fmaf(b, b, q1); }
  float q = q0 + q1;
#pragma unroll
  for (int o = 4; o; o >>= 1) q += __shfl_xor_sync(0xffffffffu, q, o);
  const float mb = bf_rn(mean);
  const float inv = fdiv(1.f, bf_rn(fsqrt(bf_rn(bf_rn(q * (1.f / DM)) + 1e-5f))));
  auto nrm = [&](int i) { const uint32_t d = pack2(f[i] - mb, f[i + 1] - mb); return pack2(bf_lo(d) * inv, bf_hi(d) * inv); };
  auto halve = [](uint32_t v) { return pack2(bf_lo(v) * 0.5f, bf_hi(v) * 0.5f); };
  uint4* g = reinterpret_cast<uint4*>(g_xn + (size_t)grow * DM) + (lane & 7);
#pragma unroll
  for (int i = 0; i < 9; i++) {
    const uint4 o = make_uint4(nrm(8 * i), nrm(8 * i + 2), nrm(8 * i + 4), nrm(8 * i + 6));
    asm volatile("st.shared.v4.u32 [%0], {%1,%2,%3,%4};" ::"r"(sb + xn_off(i) + r * 128 + (((lane ^ r) & 7) << 4)), "r"(o.x), "r"(o.y), "r"(o.z), "r"(o.w) : "memory");
    if (to_global) g[8 * i] = make_uint4(halve(o.x), halve(o.y), halve(o.z), halve(o.w));
  }
  fence_async_smem();
}

__device__ __forceinline__ void attn_row_slow(int head, int row, int lane) {
  const uint8_t* qp = g_q + (size_t)head * (SEQ * 36) + row * 36;
  float q[18], o[18];
#pragma unroll
  for (int d = 0; d < 18; d += 2) {
    const uint32_t v = __ldcg(reinterpret_cast<const uint32_t*>(qp + d * 2));
    q[d] = bf_lo(v); q[d + 1] = bf_hi(v); o[d] = 0.f; o[d + 1] = 0.f;
  }
  float m = -INFINITY, l = 0.f;
#pragma unroll 1
  for (int key = lane; key < SEQ; key += 32) {
    const uint8_t* kp = g_kv + (size_t)head * (32 * KSTB) + (key >> 3) * 640 + (key & 7) * 16;
    uint32_t wk[9], wv[9];
    auto ld18 = [&](uint32_t (&w)[9], const uint8_t* src, const uint8_t* last) {
      const uint4 a = __ldcg(reinterpret_cast<const uint4*>(src)), b = __ldcg(reinterpret_cast<const uint4*>(src + 128));
      w[0] = a.x; w[1] = a.y; w[2] = a.z; w[3] = a.w; w[4] = b.x; w[5] = b.y; w[6] = b.z; w[7] = b.w;
      w[8] = __ldcg(reinterpret_cast<const uint32_t*>(last));
    };
    ld18(wk, kp, kp + 512); ld18(wv, kp + 256, kp + 520);
    float s = 0.f;
#pragma unroll
    for (int d = 0; d < 9; d++) { s = fmaf(q[2 * d], bf_lo(wk[d]), s); s = fmaf(q[2 * d + 1], bf_hi(wk[d]), s); }
    const float mn = fmaxf(m, s), c = ex2(m - mn), p = ex2(s - mn);
    m = mn; l = l * c + p;
#pragma unroll
    for (int d = 0; d < 9; d++) { o[2 * d] = fmaf(p, bf_lo(wv[d]), o[2 * d] * c); o[2 * d + 1] = fmaf(p, bf_hi(wv[d]), o[2 * d + 1] * c); }
  }
  float M = m;
#pragma unroll
  for (int t = 16; t; t >>= 1) M = fmaxf(M, __shfl_xor_sync(0xffffffffu, M, t));
  const float c = ex2(m - M);
  l *= c;
#pragma unroll
  for (int t = 16; t; t >>= 1) l += __shfl_xor_sync(0xffffffffu, l, t);
  uint32_t* dst = reinterpret_cast<uint32_t*>(g_H + (size_t)row * HW + FF + head * 18);
#pragma unroll
  for (int d = 0; d < 18; d += 2) {
    float a = o[d] * c, b = o[d + 1] * c;
#pragma unroll
    for (int t = 16; t; t >>= 1) { a += __shfl_xor_sync(0xffffffffu, a, t); b += __shfl_xor_sync(0xffffffffu, b, t); }
    if (lane == 0) dst[d >> 1] = pack2(fdiv(a, l), fdiv(b, l));
  }
}

constexpr uint32_t AB = (BH >> 4) + (255u << 16);
template <int MODE>
__device__ __forceinline__ void gemm_run(float (&a0)[96], float (&a1)[96], int nk, int keep, int& st, uint32_t& ph, uint32_t dA,
                                         uint32_t bar_full, int lane, uint32_t& gw) {
  constexpr bool BOTH = MODE == 0;
  uint32_t da = dA + st * (GSTB >> 4);
  uint32_t rel = 0;
  int kb = 0;
  pin(a0); if (BOTH) pin(a1);
#pragma unroll 1
  do {
    wg_fence();
    const uint32_t aa = MODE != 1 ? da : dA + (xn_off(kb) >> 4);
    wgmma_ss_n192(a0, aa, da + AB, kb | keep);
    wg_commit();
    wg_wait<1>();
    if (rel) release_stage(rel, lane);
    if (BOTH) {
      wgmma_ss_n192(a1, da + 512, da + AB, kb | keep);
      wg_commit();
      wg_wait<1>();
    }
    rel = bar_full + 32 + 8 * st;
    if (++st == GST) { st = 0; ph ^= 1; }
    bool ready = false;
#pragma unroll
    for (int k = 1; k < 4; k++) {
      if (k == 3) ready = mbar_test(bar_full + 8 * st, ph);
      wgmma_ss_n192(a0, aa + 2 * k, da + AB + (k >> 1) * (BH2 >> 4) + (k & 1) * 128, 1);
      wg_commit();
      if (BOTH) {
        wg_wait<1>();
        wgmma_ss_n192(a1, da + 512 + 2 * k, da + AB + (k >> 1) * (BH2 >> 4) + (k & 1) * 128, 1);
        wg_commit();
      }
      if (k < 3) wg_wait<1>();
    }
    da = dA + st * (GSTB >> 4);
    if (++kb < nk && !ready) { TIC(t0); mbar_wait(bar_full + 8 * st, ph); TOC(gw, t0); }
    wg_wait<1>();
  } while (kb < nk);
  wg_wait<0>();
  pin(a0); if (BOTH) pin(a1);
  release_stage(rel, lane);
}

template <bool ODD>
__device__ __forceinline__ void glu_epilogue(const float (&E)[96], uint32_t s0) {
#pragma unroll
  for (int g = 0; g < 8; g += 2) {
    uint32_t h[4], w[4];
    if (ODD) ldsm4((s0 + 16384) ^ (g << 4), w[0], w[1], w[2], w[3]);
#pragma unroll
    for (int i = 0; i < 4; i++) {
      const int e = 4 * g + 2 * i;
      if (ODD) {
        h[i] = pack2(fmaf(tanhf_fast(E[64 + e]), E[32 + e], E[32 + e]), fmaf(tanhf_fast(E[65 + e]), E[33 + e], E[33 + e]));
        w[i] = pack2(bf_lo(w[i]) * E[e], bf_hi(w[i]) * E[e + 1]);
      } else {
        h[i] = pack2(fmaf(tanhf_fast(E[e]), E[64 + e], E[64 + e]), fmaf(tanhf_fast(E[e + 1]), E[65 + e], E[65 + e]));
        w[i] = pack2(tanhf_fast(E[32 + e]) + 1.f, tanhf_fast(E[33 + e]) + 1.f);
      }
    }
    stsm4(s0 ^ (g << 4), h[0], h[1], h[2], h[3]);
    stsm4((s0 + 16384) ^ (g << 4), w[0], w[1], w[2], w[3]);
  }
}

__device__ __forceinline__ void qkv_scatter(uint32_t tile, int rb, int a, int w, int hoff, int hstep, int lane) {
  const int r8 = lane >> 2, j = lane & 3;
  const int h0 = ((a * 64 * 3641) >> 16) + hoff;
  uint8_t* const qb = g_q + rb * 288 + lane * 4;
  uint8_t* const kb = g_kv + rb * 640 + r8 * 16 + j * 4;
  const uint32_t row = tile + (w * 16 + r8) * 400 + 128;
#pragma unroll 1
  for (int h = h0; h * 18 < a * 64 + 64; h += hstep) {
    uint32_t v[2][4], t[2], q[5];
    bool data[2], qd[5];
    const int col0 = h * 18 - a * 64;
#pragma unroll
    for (int i = 0; i < 5; i++) {
      const int wd = lane + 32 * i, r = (wd * 57) >> 9, col = col0 + 2 * (wd - 9 * r);
      qd[i] = wd < 144 && (unsigned)col < 64u;
      q[i] = lds32(tile + (qd[i] ? (w * 16 + r) * 400 + col * 2 : 0));
    }
#pragma unroll
    for (int c = 0; c < 2; c++) {
      const int col = col0 + c * 8 + 2 * j;
      data[c] = (unsigned)col < 64u;
      const uint32_t src = row + (data[c] ? col : 0) * 2;
#pragma unroll
      for (int e = 0; e < 4; e++) v[c][e] = lds32(src + (e >> 1) * 128 + (e & 1) * 3200);
    }
    const bool tail = (unsigned)(col0 + 16) < 64u;
    const uint32_t ts = row + (tail ? col0 + 16 : 0) * 2 + (j >> 1) * 128;
    t[0] = lds32(ts); t[1] = lds32(ts + 3200);
    if (j & 1) t[0] = t[1] = j == 1 ? 0x3f803f80u : 0u;
    uint8_t* const kp = kb + h * (32 * KSTB);
#pragma unroll
    for (int c = 0; c < 2; c++)
      if (data[c]) {
        *reinterpret_cast<uint32_t*>(kp + c * 128) = v[c][0]; *reinterpret_cast<uint32_t*>(kp + c * 128 + 640) = v[c][1];
        *reinterpret_cast<uint32_t*>(kp + c * 128 + 256) = v[c][2]; *reinterpret_cast<uint32_t*>(kp + c * 128 + 896) = v[c][3];
      }
    if (tail) { *reinterpret_cast<uint32_t*>(kp + 512) = t[0]; *reinterpret_cast<uint32_t*>(kp + 1152) = t[1]; }
    uint8_t* const qp = qb + h * (SEQ * 36);
#pragma unroll
    for (int i = 0; i < 5; i++) if (qd[i]) *reinterpret_cast<uint32_t*>(qp + i * 128) = q[i];
  }
}

__global__ void __cluster_dims__(2, 1, 1) __launch_bounds__(512, 1) fused_kernel(const __grid_constant__ Params P) {
  extern __shared__ __align__(1024) uint8_t smem_raw[];
  const uint32_t sb = (uint32_t)__cvta_generic_to_shared(smem_raw);
  if (sb & 1023u) __trap();
  const uint32_t bar_gfull = sb + OFF_BAR, bar_gempty = bar_gfull + 32;
  const uint32_t bar_kfull = bar_gfull + 256, bar_kempty = bar_kfull + 80;
  const uint32_t bar_gdone = bar_gfull + 160, bar_gfree = bar_gfull + 168, bar_odone = bar_gfull + 176, bar_qdone = bar_gfull + 184, bar_xfree = bar_gfull + 200, bar_q2done = bar_gfull + 208;
  const uint32_t bar_kpeer = bar_kfull + 160;
  const int tid = threadIdx.x;
  const int warp = __shfl_sync(0xffffffffu, tid >> 5, 0);
  const int wg = warp >> 2;
  const int cta = blockIdx.x;
  const bool att = cta < NATT;
  const int cm = cta & 15, cj = cta >> 4;
  const Sched& sch = P.sch[cta];
  const int nq = att ? 2 : 4, ngu = att ? 6 : 0;
  const int qa = att ? cta >> 5 : 8, qrow = att ? (cta & 31) * 64 : (cta - NATT) * 512;

  if (tid == 384) {
    for (int i = 0; i < GST; i++) { mbar_init(bar_gfull + 8 * i, 1); mbar_init(bar_gempty + 8 * i, 8); }
        for (int i = 0; i <= KST; i++) { mbar_init(bar_kfull + 8 * i, 1); mbar_init(bar_kempty + 8 * i, 8); }
    mbar_init(bar_kempty - 8, 8);
    mbar_init(bar_gdone, 4); mbar_init(bar_gfree, 1); mbar_init(bar_odone, 8); mbar_init(bar_qdone, 8); mbar_init(bar_xfree, 4); mbar_init(bar_q2done, 4);
    for (int i = 0; i < KST; i++) mbar_init(bar_kpeer + 8 * i, 1);
    asm volatile("fence.mbarrier_init.release.cluster;" ::: "memory");
    fence_async_smem();
    STAMP(0);
  }
  uint4 xv[9];
  const int lrow = ((warp * 4 + (qa - 1) * 16) & 63) + ((tid & 31) >> 3);
  if (att) {
    const uint4* xr = reinterpret_cast<const uint4*>(P.x + (size_t)(qrow + lrow) * DM) + (tid & 7);
#pragma unroll
    for (int i = 0; i < 9; i++) xv[i] = __ldg(xr + 8 * i);
  }
  if (tid >= 480 && tid < 492) asm volatile("prefetch.tensormap [%0];" ::"l"(&P.xn + (tid - 480)) : "memory");
  __syncwarp();
  cluster_sync();
  if (warp == 0) STAMP(30);
  const int rank = cta & 1;
  if (warp == 12)
    for (int i = 0; i < GST; i++) {
      expect1(bar_gfull + 8 * i, att ? GSTB - BH : GSTB);
      tma3d_mc(sb + i * GSTB + BH + rank * BH2, &P.wqkv, qa * 64, i * 64 + rank * 32, 0, bar_gfull + 8 * i);
    }
  if (tid == 416 && cm < 10) pf3d(&P.wqkv, qa * 64, GST * 64 + cm * 32, 0);
  if (tid == 448 && att && (cta & 31) < 18) pf3d(&P.wqkv, (qa + 4) * 64, (cta & 31) * 32, 0);
  __syncwarp();
  if (att) {
    layernorm_rows(xv, sb, lrow, qrow + lrow, wg == 1, tid & 31);
    if (warp == 0) STAMP(38);
    if (wg == 0) bar_sync(4, 512); else bar_arrive(4, 512);
    if (warp == 0) STAMP(39);
    if (wg == 1) {
      fence_async_glob();
      __syncwarp();
      if ((tid & 31) == 0) { fence_release(); red_relaxed(g_flags + FL_LN + (qrow >> 7) * 32, 4); }
    }
  }

  if (wg == 3) {
    asm volatile("setmaxnreg.dec.sync.aligned.u32 24;");
    const int pw = warp & 3, lane = lane_id();
    const bool el = lane == 0;
    if (pw == 0) {
      int st = 0; uint32_t ph = 1;
      const uint64_t pol = policy_stream();
      auto acquire = [&](uint32_t bytes) -> uint32_t {
        mbar_wait(bar_gempty + 8 * st, ph);
        expect1(bar_gfull + 8 * st, bytes);
        return sb + st * GSTB;
      };
      auto advance = [&]() { if (++st == GST) { st = 0; ph ^= 1; } };
      if (att) {
        ph ^= 1;
#pragma unroll 1
        for (int i = GST; i < 18; i++) {
          const uint32_t s = acquire(GSTB - BH);
          tma3d_mc(s + BH + rank * BH2, &P.wqkv, (i < 9 ? qa : qa + 4) * 64, (i < 9 ? i : i - 9) * 64 + rank * 32, 0, bar_gfull + 8 * st);
          advance();
        }
      } else {
#pragma unroll 1
        for (int t = 0; t < 4; t++) {
          const int row = uni(qrow + t * 128);
          int kb = 0;
          poll_ge(g_flags + FL_LN + (row >> 7) * 32, 128);
          fence_async_glob();
          if (t == 0) {
            STAMP(1);
            for (int i = 0; i < GST; i++) tma2d(sb + i * GSTB, &P.xn, i * 64, row, bar_gfull + 8 * i);
            kb = GST; ph ^= 1;
          }
          st = uni(st); ph = uni(ph); kb = uni(kb);
#pragma unroll 1
          for (; kb < 9; kb++) {
            const uint32_t s = acquire(GSTB);
            tma2d(s, &P.xn, kb * 64, row, bar_gfull + 8 * st);
            tma3d_mc(s + BH + rank * BH2, &P.wqkv, 8 * 64, kb * 64 + rank * 32, 0, bar_gfull + 8 * st);
            advance();
          }
        }
      }
      if (att) { poll_ge(g_flags + FL_LN + cm * 32, 128); fence_async_glob(); }
#pragma unroll 1
      for (int t = 0; t < ngu; t++) {
        const int a0 = uni((cj + 8 * (t >> 1)) * 3), hf = uni(t & 1);
        const CUtensorMap* m2 = hf ? &P.wu2 : &P.wg2; const CUtensorMap* m1 = hf ? &P.wg1 : &P.wu1;
        const int x2 = a0 + hf, x1 = a0 + 2 * hf;
        if (hf && t < 5 && lane < 7) {
          const int b = cm + 16 * lane;
          if (b < 108) pf3d(b < 54 ? &P.wg1 : &P.wu1, 0, ((b % 54) / 3) * 32, a0 + 24 + b % 3);
        }
        if (t == 4 && lane < 4) {
          const int b = cta + 128 * lane;
          if (b < 432) pf3d(&P.wd, 0, (b / 3) * 32, (b % 3) * 3);
          else if (b < 486) pf3d(&P.wo, 0, ((b - 432) / 3) * 32, ((b - 432) % 3) * 3);
        }
        st = uni(st); ph = uni(ph);
#pragma unroll 1
        for (int kb = 0; kb < 9; kb++) {
          const uint32_t s = acquire(GSTB), b = bar_gfull + 8 * st;
          tma2d(s, &P.xn, kb * 64, cm * 128, b);
          tma3d_mc_stream(s + BH + rank * BH2, m2, 0, kb * 64 + rank * 32, x2, b, pol);
          tma3d_mc_stream(s + BH + rank * BH2 + 8192, m1, 0, kb * 64 + rank * 32, x1, b, pol);
          advance();
        }
      }
      auto wait_h = [&](int m, int kb, int k1) -> int {
        const uint32_t t0 = clk32();
        const int i = kb + lane;
        uint32_t b;
        while (true) {
          bool ok = false;
          if (i < k1) ok = ld_relaxed(g_flags + FL_H + m * 96 + i) >= (i < 72 ? 1 : 32 + 8 * (i & 1));
          b = __ballot_sync(0xffffffffu, ok);
          if (b & 1) break;
          __nanosleep(kb >= 78 ? LSLEEP : 200);
          if (clk32() - t0 > 0x60000000u) __trap();
        }
        fence_acquire();
        fence_async_glob();
        return uni(kb + (b == 0xffffffffu ? 32 : __ffs(~b) - 1));
      };
      auto down_range = [&](int m, int n, int k0, int k1) {
#pragma unroll 1
        for (int kb = k0; kb < k1;) {
          const int ready = wait_h(m, kb, k1);
          st = uni(st); ph = uni(ph); kb = uni(kb); m = uni(m); n = uni(n);
          const CUtensorMap* mw = kb < 72 ? &P.wd : &P.wo;
          const int y0 = rank * 32 - (kb < 72 ? 0 : 72 * 64);
#pragma unroll 1
          for (; kb < ready; kb++) {
            const uint32_t s = acquire(GSTB), b = bar_gfull + 8 * st;
            tma2d(s, &P.H, kb * 64, m * 128, b);
            tma3d_mc(s + BH + rank * BH2, mw, 0, kb * 64 + y0, n * 3, b);
            advance();
          }
        }
      };
      const int kind = sch.kind;
#pragma unroll 1
      for (int i = 0; i < sch.nseg; i++) {
        const int va = sch.k0[i], vb = sch.k1[i], ne = sch.kc[i] - NL;
#pragma unroll 1
        for (int h = 0; h < (kind == 1 ? 4 : 2); h++) {
          int k0, k1;
          if (kind == 1) { k0 = h == 0 ? 72 : h == 1 ? ne : h == 2 ? 48 + NL : 76; k1 = h == 0 ? 76 : h == 1 ? 48 : h == 2 ? 72 : 78; }
          else { k0 = h ? (va > ne ? va : ne) + 48 - ne : va; k1 = h ? vb + 48 - ne : (vb < ne ? vb : ne); }
          down_range(sch.m[i], sch.n[i], k0, k1);
        }
      }
      if (kind) {
        const int m = sch.m[0], n = sch.n[0], tile = m * 3 + n, row = m * 128 + (kind - 1) * 64;
        {
          const uint32_t s = acquire(24576);
          for (int c = 0; c < 3; c++) tma2d(s + c * 8192, &P.xin, n * 192 + c * 64, row, bar_gfull + 8 * st);
          advance();
        }
#pragma unroll 1
        for (int p = 0; p < 2; p++) {
          poll_ge(g_flags + FL_P + tile * 3 + p * (3 - kind), 1);
          fence_async_glob();
          const uint32_t s = acquire(24576);
          bulk_load(s, g_part + (tile * 4 + p * 2 + kind - 1) * 1536, 24576, bar_gfull + 8 * st, pol);
          advance();
        }
#pragma unroll 1
        for (int kb = 78; kb < 81;) {
          const int ready = wait_h(m, kb, 81);
          st = uni(st); ph = uni(ph); kb = uni(kb);
#pragma unroll 1
          for (; kb < ready; kb++) {
            const uint32_t s = acquire(GSTB - 8192), b = bar_gfull + 8 * st;
            tma2d(s, &P.H64, kb * 64, row, b);
            tma3d_mc(s + BH + rank * BH2, &P.wo, 0, (kb - 72) * 64 + rank * 32, n * 3, b);
            advance();
          }
        }
      }
    } else if (pw == 1) {
      if (att) {
        const uint64_t pol = policy_stream();
        const uint32_t peer = map_peer(bar_kpeer, rank ^ 1);
        uint32_t st = 0, ph = 0;
        int m = 0;
#pragma unroll 1
        for (int r = 0; r < 5; r++) {
          if (r < 4) {
            const int head = r * 8 + cj, atom = (head * 18 + (lane & 1) * 17) >> 6;
            poll_ge(g_flags + FL_QKV + atom * 32, atom < 8 ? 256 : 128);
            fence_async_glob();
            mbar_wait(bar_kempty + 8 * KST, (r & 1) ^ 1);
            expect1(bar_kfull + 8 * KST, QB);
            bulk_load(sb + OFF_Q, g_q + head * (SEQ * 36) + cm * QB, QB, bar_kfull + 8 * KST, pol);
            if (r == 0) STAMP(2);
          }
          if (r == 0) mbar_wait(bar_xfree, 0);
          const int mend = uni(r < 3 ? r * 32 + 27 : (r == 3 ? 0 : 128));
          st = uni(st); ph = uni(ph); m = uni(m);
#pragma unroll 1
          for (; m < mend; m++) {
            mbar_wait(bar_kempty + 8 * st, ph ^ 1);
            expect1(bar_kfull + 8 * st, KSTB);
            if ((m & 1) == rank) {
              mbar_wait(bar_kpeer + 8 * st, ph);
              bulk_load_mc(sb + OFF_KV + st * KSTB, g_kv + (uint32_t)((((m >> 5) * 8 + cj) * 32 + (m & 31)) * KSTB), KSTB, bar_kfull + 8 * st, pol);
            } else arrive_cluster1(peer + 8 * st);
            if (++st == KST) { st = 0; ph ^= 1; }
          }
        }
      }
    } else if (pw == 2) {
      if (att) {
        mbar_wait(bar_qdone, 0);
        mbar_wait(bar_qdone, 1);
        mbar_wait(bar_q2done, 0);
        if (el) { fence_async_glob(); fence_release(); red_relaxed(g_flags + FL_QKV + (qa + 4) * 32, 8); }
        __syncwarp();
      }
      const int nt = ngu + sch.nseg;
#pragma unroll 1
      for (int u = 0; u < nt; u++) {
        mbar_wait(bar_gdone, u & 1);
        if (el) {
          if (u < ngu) {
            const int a0 = (cj + 8 * (u >> 1)) * 3;
            if (u & 1) { tma2d_store(&P.H, (a0 + 1) * 64, cm * 128, sb + OFF_STG + 16384); tma2d_store(&P.H, (a0 + 2) * 64, cm * 128, sb + OFF_STG); }
            else tma2d_store(&P.H, a0 * 64, cm * 128, sb + OFF_STG);
            bulk_commit(); bulk_wait0();
            fence_release();
            if (u & 1) { red_relaxed(g_flags + FL_H + cm * 96 + a0 + 1); red_relaxed(g_flags + FL_H + cm * 96 + a0 + 2); }
            else red_relaxed(g_flags + FL_H + cm * 96 + a0);
          } else {
            fence_async_glob();
            red_release(g_flags + FL_P + (sch.m[u - ngu] * 3 + sch.n[u - ngu]) * 3 + sch.kind);
          }
          mbar_arrive(bar_gfree);
          if (u == ngu - 1) STAMP(35);
          if (u == nt - 1) STAMP(36);
        }
        __syncwarp();
      }
    } else {
      if (att) {
        if (lane < 7) {
          const int b = cm + 16 * lane;
          if (b < 108) pf3d(b < 54 ? &P.wg1 : &P.wu1, 0, ((b % 54) / 3) * 32, cj * 3 + b % 3);
        }
        for (int r = 0; r < 3; r++) {
          mbar_wait(bar_odone, r & 1);
          if (el) {
            const int head = r * 8 + cj, a0 = (head * 18) >> 6, a1 = (head * 18 + 17) >> 6;
            fence_async_glob();
            fence_release();
            red_relaxed(g_flags + FL_H + cm * 96 + 72 + a0, 8);
            if (a1 != a0) red_relaxed(g_flags + FL_H + cm * 96 + 72 + a1, 8);
          }
          __syncwarp();
        }
      }
    }
    if (pw == 0 || (pw == 1 && att)) {
      int old = 0;
      if (el) { __threadfence(); old = atomicAdd(g_flags + FL_DONE, 1); __threadfence(); }
      old = __shfl_sync(0xffffffffu, old, 0);
      if (old == NCTA + NATT - 1) for (int i = lane; i < FL_TOTAL; i += 32) g_flags[i] = 0;
    }
  } else if (wg >= 1) {
    const int lane = lane_id();
#pragma unroll 1
    for (int t = 0; t < nq; t++) {
      bar_sync(1, 384);
      if (att) qkv_scatter(sb + OFF_STG, (qrow >> 3) + (warp & 3) * 2, qa + 4 * t, warp & 3, wg - 1, 2 + t, lane);
      else qkv_scatter(sb + OFF_STG, (qrow >> 3) + t * 16 + (warp - 4) * 2, 8, warp - 4, 0, 1, lane);
      if (att && t) fence_cta(); else fence_async_glob();
      __syncwarp();
      if (lane == 0) {
        if (!att || !t) red_release(g_flags + FL_QKV + qa * 32);
        mbar_arrive(bar_qdone);
      }
      if (warp == 4) STAMP(t ? 34 : 32);
    }
    if (att) {
      const int wa = warp - 4;
      const int r8 = lane >> 2, j = lane & 3;
      const uint32_t kvd = __shfl_sync(0xffffffffu, desc_lo(sb + OFF_KV, 0), 0);
      const uint32_t kb0 = __shfl_sync(0xffffffffu, bar_kfull, 0);
      constexpr uint32_t DK = 8u << 16, DK2 = 32, DV = (40u << 16) + 16;
      const uint32_t qa = sb + OFF_Q + (wa * 16 + r8) * 36 + j * 4;
      uint32_t q[8], p[16];
      float s[32], s2[32], o[12];
      auto load_q = [&](int r) {
        mbar_wait(kb0 + 8 * KST, r & 1);
        q[0] = lds32(qa); q[1] = lds32(qa + 288); q[2] = lds32(qa + 16); q[3] = lds32(qa + 304);
        q[4] = j == 0 ? lds32(qa + 32) : 0u; q[5] = j == 0 ? lds32(qa + 320) : 0u; q[6] = 0u; q[7] = 0u;
      };
      load_q(0);
      mbar_wait(kb0, 0);
      pin(q);
      wg_fence();
      wgmma_rs_n64<40, 0>(s, q[0], q[1], q[2], q[3], kvd + DK);
      wgmma_rs_n64<40, 1>(s, q[4], q[5], q[6], q[7], kvd + DK2);
      wg_commit();
      mbar_wait(kb0 + 8, 0);
      wg_wait<0>();
      pin(s);
#pragma unroll
      for (int i = 0; i < 32; i++) s2[i] = 0.f;
#pragma unroll
      for (int i = 0; i < 16; i++) p[i] = 0u;
      uint32_t cur = uni(1), prev = uni(0), old = uni(-1), nph = uni(0);
      auto step = [&](float (&a)[32], float (&b)[32], bool special) {
        const uint32_t d = kvd + cur * (KSTB >> 4);
        const uint32_t nxt = cur + 1 == KST ? 0 : cur + 1;
        nph ^= nxt == 0;
        pin(b); pin(q);
        wg_fence();
        wgmma_rs_n64<40, 0>(b, q[0], q[1], q[2], q[3], d + DK);
        wgmma_rs_n64<40, 1>(b, q[4], q[5], q[6], q[7], d + DK2);
        wg_commit();
#pragma unroll
        for (int i = 0; i < 32; i++) a[i] = ex2(a[i]);
        pin(a);
        wg_wait<1>();
        pin(p); pin(o);
        arrive1(kb0 + 80 + 8 * old);
        const bool ready = mbar_test(kb0 + 8 * nxt, nph);
#pragma unroll
        for (int i = 0; i < 16; i++) p[i] = pack2(a[2 * i], a[2 * i + 1]);
        pin(p);
        wg_fence();
#pragma unroll
        for (int k = 0; k < 4; k++)
          wgmma_rs_n24<8, 1>(o, p[4 * k], p[4 * k + 1], p[4 * k + 2], p[4 * k + 3], kvd + prev * (KSTB >> 4) + DV + k * 80);
        wg_commit();
        if (!ready && !special) mbar_wait(kb0 + 8 * nxt, nph);
        wg_wait<1>();
        pin(b);
        old = prev; prev = cur; cur = nxt;
      };
      auto new_rows = [&]() {
        if (lane == 0) mbar_arrive(kb0 + 80 + 8 * KST);
        {
          float m0 = fmaxf(s[0], s[1]), m1 = fmaxf(s[2], s[3]);
#pragma unroll
          for (int i = 4; i < 32; i += 4) { m0 = fmaxf(m0, fmaxf(s[i], s[i + 1])); m1 = fmaxf(m1, fmaxf(s[i + 2], s[i + 3])); }
          m0 = fmaxf(m0, __shfl_xor_sync(0xffffffffu, m0, 1)); m1 = fmaxf(m1, __shfl_xor_sync(0xffffffffu, m1, 1));
          m0 = fmaxf(m0, __shfl_xor_sync(0xffffffffu, m0, 2)); m1 = fmaxf(m1, __shfl_xor_sync(0xffffffffu, m1, 2));
          m0 = -(m0 + MBIAS); m1 = -(m1 + MBIAS);
          const float h0 = bf_rn(m0), h1 = bf_rn(m1), l0 = bf_rn(m0 - h0), l1 = bf_rn(m1 - h1);
          if (j == 1) { q[4] = pack2(h0, l0); q[5] = pack2(h1, l1); }
          m0 = h0 + l0; m1 = h1 + l1;
#pragma unroll
          for (int i = 0; i < 32; i += 4) { s[i] += m0; s[i + 1] += m0; s[i + 2] += m1; s[i + 3] += m1; }
        }
      };
      new_rows();
#pragma unroll 1
      for (int r = 0; r < 4; r++) {
        const int head = r * 8 + cj;
        TIC(tb);
#pragma unroll
        for (int i = 0; i < 12; i++) o[i] = 0.f;
        TOC(aw, tb);
        const int nq1 = uni(r < 3 ? 15 : -1), nl = uni(r == 3 ? 15 : -1);
        nph = uni(nph);
#pragma unroll 1
        for (int n = uni(0); n < 16; n++) {
          step(s, s2, n == nl);
          if (n == nq1) load_q(r + 1);
          step(s2, s, n == nl);
        }
        if (r < 3) new_rows();
        wg_wait<0>();
        pin(o); pin(s);
        TIC(te);
        const float l0 = __shfl_sync(0xffffffffu, o[8], (lane & ~3) | 1), l1 = __shfl_sync(0xffffffffu, o[10], (lane & ~3) | 1);
        float lo0 = fminf(fminf(fabsf(o[0]), fabsf(o[1])), fminf(fabsf(o[4]), fabsf(o[5])));
        float lo1 = fminf(fminf(fabsf(o[2]), fabsf(o[3])), fminf(fabsf(o[6]), fabsf(o[7])));
        float z0 = (o[0] + o[1] + o[4] + o[5]) * 0.f, z1 = (o[2] + o[3] + o[6] + o[7]) * 0.f;
        if (j == 2) {
          lo0 = fminf(lo0, fminf(fabsf(o[8]), fabsf(o[9]))); lo1 = fminf(lo1, fminf(fabsf(o[10]), fabsf(o[11])));
          z0 += (o[8] + o[9]) * 0.f; z1 += (o[10] + o[11]) * 0.f;
        }
        const bool ok0 = l0 >= 0x1p-90f && l0 <= 0x1p125f && lo0 >= l0 * 0x1p-33f && z0 == 0.f;
        const bool ok1 = l1 >= 0x1p-90f && l1 <= 0x1p125f && lo1 >= l1 * 0x1p-33f && z1 == 0.f;
        const int row = cm * 128 + wa * 16 + r8;
        {
          const float i0 = fdiv(1.f, l0), i1 = fdiv(1.f, l1);
          uint32_t* d0 = reinterpret_cast<uint32_t*>(g_H + (size_t)row * HW + FF + head * 18) + j;
          uint32_t* d1 = d0 + 8 * (HW / 2);
          d0[0] = pack2(o[0] * i0, o[1] * i0); d0[4] = pack2(o[4] * i0, o[5] * i0);
          d1[0] = pack2(o[2] * i1, o[3] * i1); d1[4] = pack2(o[6] * i1, o[7] * i1);
          if (j == 2) { d0[6] = pack2(o[8] * i0, o[9] * i0); d1[6] = pack2(o[10] * i1, o[11] * i1); }
        }
        const uint32_t bad0 = __ballot_sync(0xffffffffu, !ok0), bad1 = __ballot_sync(0xffffffffu, !ok1);
        if (bad0 | bad1) {
          __syncwarp();
#pragma unroll 1
          for (int rr = 0; rr < 16; rr++)
            if (((rr < 8 ? bad0 : bad1) >> ((rr & 7) * 4)) & 15u) attn_row_slow(head, cm * 128 + wa * 16 + rr, lane);
        }
        if (r < 3) {
          fence_cta();
          __syncwarp();
          if (lane == 0) mbar_arrive(bar_odone);
        } else {
          fence_async_glob();
          __syncwarp();
          if (lane == 0) {
            const int a0 = (head * 18) >> 6, a1 = (head * 18 + 17) >> 6;
            fence_release();
            red_relaxed(g_flags + FL_H + cm * 96 + 72 + a0);
            if (a1 != a0) red_relaxed(g_flags + FL_H + cm * 96 + 72 + a1);
          }
        }
        TOC(aw, te);
        if (wa == 0) { STAMP(4 + r); PUT(56, aw); PUT(57, am); PUT(59, nr); PUT(60 + r, ak); }
        if (wa == 4) { PUT(24 + r, clk32() - c0); PUT(28, nr); PUT(58, clk32() - c0); }
      }
    }
  } else {
    const int lane = lane_id();
    float acc0[96], acc1[96];
#pragma unroll
    for (int i = 0; i < 96; i++) asm volatile("" : "=f"(acc0[i]));
    int st = 0; uint32_t ph = 0;
    const uint32_t dA = __shfl_sync(0xffffffffu, desc_lo(sb, 16), 0);
    uint32_t gw = 0;
    auto st_qkv = [&](float (&acc)[96], uint32_t off, float xs) {
      const float qs = 0.23570226039551584f * 1.4426950408889634f;
      const uint32_t pa = sb + OFF_STG + off + (warp * 16 + (lane & 15)) * 400 + (lane >> 4) * 16;
#pragma unroll
      for (int g = 0; g < 24; g += 2) {
        const float f = g < 8 ? qs * xs : xs;
        stsm4(pa + g * 16, pack2(acc[4 * g] * f, acc[4 * g + 1] * f), pack2(acc[4 * g + 2] * f, acc[4 * g + 3] * f),
              pack2(acc[4 * g + 4] * f, acc[4 * g + 5] * f), pack2(acc[4 * g + 6] * f, acc[4 * g + 7] * f));
      }
    };
    if (att) {
#pragma unroll 1
      for (int t = 0; t < 2; t++) {
        mbar_wait(bar_gfull + 8 * st, ph);
        GP(if (warp == 0 && t == 0) STAMP(31);)
        gemm_run<1>(acc0, acc0, 9, 0, st, ph, dA, bar_gfull, lane, gw);
        GP(if (warp == 0) { STAMP(8); if (t == 0) STAMP(43); })
        if (t) {
          if (lane == 0) mbar_arrive(bar_xfree);
          mbar_wait(bar_qdone, 0);
        }
        st_qkv(acc0, 0, 1.f);
        bar_arrive(1, 384);
        GP(if (warp == 0 && t == 0) STAMP(33);)
      }
      __syncwarp();
      qkv_scatter(sb + OFF_STG, (qrow >> 3) + warp * 2, qa + 4, warp, 2, 3, lane);
      fence_cta();
      __syncwarp();
      if (lane == 0) mbar_arrive(bar_q2done);
      GP(if (warp == 0) STAMP(9);)
    }
    asm volatile("setmaxnreg.inc.sync.aligned.u32 232;");
#pragma unroll
    for (int i = 0; i < 96; i++) asm volatile("" : "=f"(acc0[i]), "=f"(acc1[i]));
    const uint32_t soff = (warp * 16 + (lane & 15)) * 128 + (((lane >> 4) ^ (lane & 7)) << 4);
    if (!att) {
#pragma unroll 1
      for (int t = 0; t < 4; t++) {
        mbar_wait(bar_gfull + 8 * st, ph);
        gemm_run<0>(acc0, acc1, 9, 0, st, ph, dA, bar_gfull, lane, gw);
        GP(if (warp == 0) STAMP(8);)
        if (t) mbar_wait(bar_qdone, (t - 1) & 1);
        st_qkv(acc0, 0, 2.f); st_qkv(acc1, 64 * 400, 2.f);
        bar_arrive(1, 384);
        GP(if (warp == 0) { STAMP(9); if (t == 0) STAMP(33); })
      }
    }
#pragma unroll 1
    for (int u = 0; u < ngu; u++) {
      mbar_wait(bar_gfull + 8 * st, ph);
      gemm_run<0>(acc0, acc1, 9, 0, st, ph, dA, bar_gfull, lane, gw);
      GP(if (warp == 0) STAMP(10 + 2 * u);)
      if (u) mbar_wait(bar_gfree, (u - 1) & 1); else mbar_wait(bar_qdone, 1);
      const uint32_t s4 = sb + OFF_STG + soff;
      if (u & 1) { glu_epilogue<true>(acc0, s4); glu_epilogue<true>(acc1, s4 + 8192); }
      else { glu_epilogue<false>(acc0, s4); glu_epilogue<false>(acc1, s4 + 8192); }
      fence_async_smem();
      __syncwarp();
      if (lane == 0) mbar_arrive(bar_gdone);
      GP(if (warp == 0) STAMP(11 + 2 * u);)
    }
    const int kind = sch.kind;
#pragma unroll 1
    for (int sg = 0; sg < sch.nseg; sg++) {
      mbar_wait(bar_gfull + 8 * st, ph);
      gemm_run<0>(acc0, acc1, kind == 1 ? 78 - sch.kc[0] : sch.k1[sg] - sch.k0[sg], 0, st, ph, dA, bar_gfull, lane, gw);
      GP(if (warp == 0) STAMP(10 + 2 * (ngu + sg));)
      uint4* pp = g_part + ((sch.m[sg] * 3 + sch.n[sg]) * 4 + (kind ? 2 : 0)) * 1536 + warp * 32 + lane;
      auto put = [&](const float (&acc)[96], uint4* q) {
#pragma unroll
        for (int i = 0; i < 12; i++)
          q[i * 128] = make_uint4(pack2(acc[8 * i], acc[8 * i + 1]), pack2(acc[8 * i + 2], acc[8 * i + 3]),
                                  pack2(acc[8 * i + 4], acc[8 * i + 5]), pack2(acc[8 * i + 6], acc[8 * i + 7]));
      };
      if (kind != 1) put(acc0, pp);
      if (kind != 2) put(acc1, pp + 1536);
      fence_cta();
      if (ngu + sg) mbar_wait(bar_gfree, (ngu + sg - 1) & 1);
      __syncwarp();
      if (lane == 0) mbar_arrive(bar_gdone);
      GP(if (warp == 0) STAMP(11 + 2 * (ngu + sg));)
    }
    if (kind) {
      if (kind == 2) {
#pragma unroll
        for (int i = 0; i < 96; i++) acc0[i] = acc1[i];
      }
      {
        mbar_wait(bar_gfull + 8 * st, ph);
        uint32_t dep = 0;
#pragma unroll
        for (int g = 0; g < 24; g += 2) {
          uint32_t w[4];
          ldsm4((sb + st * GSTB + (g >> 3) * 8192 + soff) ^ ((g & 7) << 4), w[0], w[1], w[2], w[3]);
          dep |= w[3];
#pragma unroll
          for (int i = 0; i < 4; i++) { acc0[4 * g + 2 * i] += bf_lo(w[i]); acc0[4 * g + 2 * i + 1] += bf_hi(w[i]); }
        }
        release_stage(bar_gempty + 8 * st + (dep & P.zero), lane);
        if (++st == GST) { st = 0; ph ^= 1; }
      }
#pragma unroll 1
      for (int pp = 0; pp < 2; pp++) {
        mbar_wait(bar_gfull + 8 * st, ph);
        const uint32_t a = sb + st * GSTB + (warp * 32 + lane) * 16;
        uint32_t dep = 0;
#pragma unroll
        for (int i = 0; i < 12; i++) {
          const uint4 v = lds128(a + i * 2048);
          dep |= v.w;
          acc0[8 * i] += bf_lo(v.x); acc0[8 * i + 1] += bf_hi(v.x); acc0[8 * i + 2] += bf_lo(v.y); acc0[8 * i + 3] += bf_hi(v.y);
          acc0[8 * i + 4] += bf_lo(v.z); acc0[8 * i + 5] += bf_hi(v.z); acc0[8 * i + 6] += bf_lo(v.w); acc0[8 * i + 7] += bf_hi(v.w);
        }
        release_stage(bar_gempty + 8 * st + (dep & P.zero), lane);
        if (++st == GST) { st = 0; ph ^= 1; }
      }
      GP(if (warp == 0) STAMP(40);)
      mbar_wait(bar_gfull + 8 * st, ph);
      gemm_run<2>(acc0, acc1, 3, 1, st, ph, dA, bar_gfull, lane, gw);
      GP(if (warp == 0) STAMP(41);)
#pragma unroll
      for (int g = 0; g < 24; g += 2)
        stsm4((sb + OFF_STG + (g >> 3) * 8192 + soff) ^ ((g & 7) << 4), pack2(acc0[4 * g], acc0[4 * g + 1]), pack2(acc0[4 * g + 2], acc0[4 * g + 3]),
              pack2(acc0[4 * g + 4], acc0[4 * g + 5]), pack2(acc0[4 * g + 6], acc0[4 * g + 7]));
      fence_async_smem();
      bar_sync(12, 128);
      if (warp == 0 && lane == 0) {
        for (int a = 0; a < 3; a++) tma2d_store(&P.out, sch.n[0] * 192 + a * 64, sch.m[0] * 128 + (kind - 1) * 64, sb + OFF_STG + a * 8192);
        bulk_commit();
        asm volatile("cp.async.bulk.wait_group.read 0;" ::: "memory");
      }
      if (warp == 0) STAMP(42);
    }
  }
  __syncwarp();
  cluster_sync();
}

typedef CUresult (*EncodeFn)(CUtensorMap*, CUtensorMapDataType, cuuint32_t, void*, const cuuint64_t*, const cuuint64_t*, const cuuint32_t*,
                             const cuuint32_t*, CUtensorMapInterleave, CUtensorMapSwizzle, CUtensorMapL2promotion, CUtensorMapFloatOOBfill);

void make_map(EncodeFn enc, CUtensorMap* m, const void* ptr, int rank, uint64_t d0, uint64_t d1, uint64_t d2, uint64_t s1, uint64_t s2,
              uint32_t b0, uint32_t b1, uint32_t b2) {
  cuuint64_t gd[3] = {d0, d1, d2}, gs[2] = {s1, s2};
  cuuint32_t bd[3] = {b0, b1, b2}, es[3] = {1, 1, 1};
  enc(m, CU_TENSOR_MAP_DATA_TYPE_BFLOAT16, rank, const_cast<void*>(ptr), gd, gs, bd, es, CU_TENSOR_MAP_INTERLEAVE_NONE,
      CU_TENSOR_MAP_SWIZZLE_128B, CU_TENSOR_MAP_L2_PROMOTION_L2_128B, CU_TENSOR_MAP_FLOAT_OOB_FILL_NONE);
}

void build_schedule(Sched* s) {
  for (int i = 0; i < NCTA; i++) s[i] = Sched{};
  auto add = [&](int pair, int kind, int tp, int k0, int k1, int kc) {
    for (int r = 0; r < 2; r++) {
      Sched& c = s[2 * pair + r];
      c.kind = kind; c.m[c.nseg] = 2 * (tp / 3) + r; c.n[c.nseg] = tp % 3; c.k0[c.nseg] = k0; c.k1[c.nseg] = k1; c.kc[c.nseg] = kc; c.nseg++;
    }
  };
  for (int t = 0; t < 24; t++) {
    const int c = t < 8 ? CF : C1, kc = c + (t < 8 ? C3 : C2);
    add(t < 8 ? 64 + t / 4 : 40 + t, 0, t, 0, c, kc);
    add(t, 1, t, 0, 0, kc);
    add(24 + t, 2, t, c, kc, kc);
  }
}

}

extern "C" void kernel_launch(void* const* d_in, const int* in_sizes, int n_in, void* d_out, int out_size) {
  static EncodeFn enc = nullptr;
  if (!enc) {
    void* f = nullptr; cudaDriverEntryPointQueryResult q;
    cudaGetDriverEntryPoint("cuTensorMapEncodeTiled", &f, cudaEnableDefault, &q);
    enc = (EncodeFn)f;
    cudaFuncSetAttribute(fused_kernel, cudaFuncAttributeMaxDynamicSharedMemorySize, SMEM_BYTES);
  }
  void *xn, *H;
  cudaGetSymbolAddress(&xn, g_xn);
  cudaGetSymbolAddress(&H, g_H);
  Params P;
  P.x = (const __nv_bfloat16*)d_in[0];
  P.zero = 0; P.pad = 0;
  make_map(enc, &P.xn, xn, 2, DM, SEQ, 1, DM * 2, 0, 64, 128, 1);
  make_map(enc, &P.xin, d_in[0], 2, DM, SEQ, 1, DM * 2, 0, 64, 64, 1);
  make_map(enc, &P.H64, H, 2, HW, SEQ, 1, HW * 2, 0, 64, 64, 1);
  make_map(enc, &P.H, H, 2, HW, SEQ, 1, HW * 2, 0, 64, 128, 1);
  make_map(enc, &P.out, d_out, 2, DM, SEQ, 1, DM * 2, 0, 64, 64, 1);
  make_map(enc, &P.wqkv, d_in[1], 3, DM, DM, 3, 3 * DM * 2, DM * 2, 64, 32, 3);
  make_map(enc, &P.wg1, d_in[4], 3, 64, DM, 72, FF * 2, 128, 64, 32, 1);
  make_map(enc, &P.wu1, d_in[5], 3, 64, DM, 72, FF * 2, 128, 64, 32, 1);
  make_map(enc, &P.wg2, d_in[4], 3, 64, DM, 72, FF * 2, 128, 64, 32, 2);
  make_map(enc, &P.wu2, d_in[5], 3, 64, DM, 72, FF * 2, 128, 64, 32, 2);
  make_map(enc, &P.wd, d_in[6], 3, 64, FF, 9, DM * 2, 128, 64, 32, 3);
  make_map(enc, &P.wo, d_in[2], 3, 64, DM, 9, DM * 2, 128, 64, 32, 3);
  build_schedule(P.sch);
  fused_kernel<<<NCTA, 512, SMEM_BYTES>>>(P);
}
```
